```python
import torch

def _softmax(x, axis=-1):
    return torch.softmax(x, dim=axis)

def _gelu(x):
    return torch.nn.functional.gelu(x, approximate='tanh')

def _silu(x):
    return torch.nn.functional.silu(x)

def _sigmoid(x):
    return torch.sigmoid(x)

def _layernorm(x, axis=-1, eps=1e-05):
    m = x.mean(dim=axis, keepdim=True)
    v = x.var(dim=axis, keepdim=True, unbiased=False)
    return (x - m) / torch.sqrt(v + eps)

def _scatter_add(tgt, idx, src, axis=0):
    return tgt.clone().index_add_(axis, idx, src)

def _segment_sum(src, seg, n):
    out = torch.zeros((n,) + src.shape[1:], dtype=src.dtype)
    return out.index_add_(0, seg, src)

def _pad(x, pw):
    flat = tuple((v for pair in reversed(pw) for v in pair))
    return torch.nn.functional.pad(x, flat)
kernel_name = 'standalone__autoregressive_conv_wavenet__speech'

def setup_inputs():

    _w = lambda a: (lambda t: t.to(torch.bfloat16) if t.is_floating_point() else t)(torch.as_tensor(a))
    B, T, D, K = (2, 1000, 512, 5)
    return {'x': _w((lambda *s: torch.randn(*s, dtype=torch.bfloat16) * 0.1)(B, T, D)), 'w': _w((lambda *s: torch.randn(*s, dtype=torch.bfloat16) * 0.1)(K, D, 2 * D)), 'w_o': _w((lambda *s: torch.randn(*s, dtype=torch.bfloat16) * 0.05)(D, D))}

def reference(x, w, w_o):
    B, T, D = x.shape
    K = w.shape[0]
    dil = 2
    pad = (K - 1) * dil
    xp = _pad(x, ((0, 0), (pad, 0), (0, 0)))
    h = torch.einsum('btc,cd->btd', xp[:, pad:pad + T, :], w[0])
    for i in range(1, K):
        off = pad - i * dil
        h = h + torch.einsum('btc,cd->btd', xp[:, off:off + T, :], w[i])
    f = h[..., :D].clone()
    g = h[..., D:].clone()
    z = torch.tanh(f) * _sigmoid(g)
    return z @ w_o
```

```cpp
#include <cuda_runtime.h>
#include <cuda_bf16.h>
#include <cuda.h>
#include <stdint.h>

namespace {

constexpr int T_LEN = 1000;
constexpr int TILE_U = 63;
constexpr int ARR_BYTES = 132 * 128;
constexpr int ARR_SLOT = 17408;
constexpr int W_BYTES = 64 * 128;
constexpr int OFF_EO = 0;
constexpr int OFF_S = 3 * 2 * ARR_SLOT;
constexpr int OFF_W = OFF_S + 2 * ARR_SLOT;
constexpr int OFF_BAR = OFF_W + 2 * 5 * W_BYTES;
constexpr int SMEM_BYTES = OFF_BAR + 1280 + 1024;
constexpr int NTHREADS = 384;
constexpr uint32_t SPIN_LIMIT = 1u << 22;
#define LOOKA 0
#define MBOX_K 4
#define ZDELAY 450
#define ZBUF(b) ((b) == 0 ? OFF_EO + 2 * ARR_SLOT : (b) == 1 ? OFF_EO + 2 * ARR_SLOT + 16384 : (b) == 2 ? OFF_S + ARR_SLOT : OFF_W + 5 * W_BYTES)
#define YBUF(p) (OFF_W + ((p) >> 2) * 5 * W_BYTES + 4 * W_BYTES + ((p) & 3) * 2048)
#define ZBAR(b) ((b) == 0 ? 3 : 12 + (b))
#define WOBUF(b) ((b) == 0 ? OFF_EO + 4 * ARR_SLOT : (b) == 1 ? OFF_EO : (b) == 2 ? OFF_W : OFF_S)
#define WOLBO(b) ((b) == 3 ? OFF_W + 7 * W_BYTES - OFF_S : 16384)
#define EPI_BAR(p) ((p) < 4 ? 4 + (p) : 5 + (p))
#define TICKS(g) ((g) == 1 ? 0 : (g) == 3 ? 1 : (g) == 5 ? 2 : (g) == 7 ? 3 : -1)

__device__ uint4 g_z[8 * 4 * 32 * 128];
__device__ unsigned g_epoch[128];
__device__ unsigned g_init[8 * 32];
__device__ unsigned g_dbg[256];
#define TS(i)

__device__ __forceinline__ uint32_t smem_u32(const void* p) { return (uint32_t)__cvta_generic_to_shared(p); }
__device__ __forceinline__ void mbar_init(uint32_t bar, uint32_t cnt) { asm volatile("mbarrier.init.shared::cta.b64 [%0], %1;" :: "r"(bar), "r"(cnt)); }
__device__ __forceinline__ void mbar_expect_tx(uint32_t bar, uint32_t bytes) { asm volatile("mbarrier.arrive.expect_tx.shared::cta.b64 _, [%0], %1;" :: "r"(bar), "r"(bytes) : "memory"); }
__device__ __forceinline__ void mbar_arrive(uint32_t bar) { asm volatile("mbarrier.arrive.shared::cta.b64 _, [%0];" :: "r"(bar) : "memory"); }
__device__ __forceinline__ void mbar_wait(uint32_t bar, uint32_t parity) {
  asm volatile("{\n.reg .pred p;\nWAIT_%=:\nmbarrier.try_wait.parity.shared::cta.b64 p, [%0], %1;\n@p bra DONE_%=;\nbra WAIT_%=;\nDONE_%=:\n}" :: "r"(bar), "r"(parity) : "memory");
}
__device__ __forceinline__ void mbar_wait_cl(uint32_t bar, uint32_t parity) {
  asm volatile("{\n.reg .pred p;\nWAIT_%=:\nmbarrier.try_wait.parity.shared::cta.b64 p, [%0], %1;\n@p bra DONE_%=;\nbra WAIT_%=;\nDONE_%=:\n}" :: "r"(bar), "r"(parity) : "memory");
}
__device__ __forceinline__ uint32_t mapa(uint32_t addr, uint32_t rank) { uint32_t r; asm("mapa.shared::cluster.u32 %0, %1, %2;" : "=r"(r) : "r"(addr), "r"(rank)); return r; }
__device__ __forceinline__ void mbar_arrive_remote(uint32_t bar_cluster_addr) { asm volatile("mbarrier.arrive.shared::cluster.b64 _, [%0];" :: "r"(bar_cluster_addr) : "memory"); }
__device__ __forceinline__ void bulk_s2s(uint32_t dst_cluster, uint32_t src, uint32_t bytes, uint32_t bar_cluster) {
  asm volatile("cp.async.bulk.shared::cluster.shared::cta.mbarrier::complete_tx::bytes [%0], [%1], %2, [%3];" :: "r"(dst_cluster), "r"(src), "r"(bytes), "r"(bar_cluster) : "memory");
}
__device__ __forceinline__ void bulk_g2s(uint32_t dst, const void* src, uint32_t bytes, uint32_t bar) {
  asm volatile("cp.async.bulk.shared::cluster.global.mbarrier::complete_tx::bytes [%0], [%1], %2, [%3];" :: "r"(dst), "l"(src), "r"(bytes), "r"(bar) : "memory");
}
__device__ __forceinline__ void tma4d_mc(uint32_t dst, const CUtensorMap* m, int c0, int c1, int c2, int c3, uint32_t bar, uint16_t mask) {
  asm volatile("cp.async.bulk.tensor.4d.shared::cluster.global.mbarrier::complete_tx::bytes.multicast::cluster [%0], [%1, {%3, %4, %5, %6}], [%2], %7;"
               :: "r"(dst), "l"(m), "r"(bar), "r"(c0), "r"(c1), "r"(c2), "r"(c3), "h"(mask) : "memory");
}
__device__ __forceinline__ void cluster_arrive() { asm volatile("barrier.cluster.arrive.relaxed.aligned;" ::: "memory"); }
__device__ __forceinline__ void cluster_arrive_rel() { asm volatile("barrier.cluster.arrive.release.aligned;" ::: "memory"); }
__device__ __forceinline__ void cluster_wait() { asm volatile("barrier.cluster.wait.acquire.aligned;" ::: "memory"); }
__device__ __forceinline__ void tma4d(uint32_t dst, const CUtensorMap* m, int c0, int c1, int c2, int c3, uint32_t bar) {
  asm volatile("cp.async.bulk.tensor.4d.shared::cluster.global.mbarrier::complete_tx::bytes [%0], [%1, {%3, %4, %5, %6}], [%2];"
               :: "r"(dst), "l"(m), "r"(bar), "r"(c0), "r"(c1), "r"(c2), "r"(c3) : "memory");
}
__device__ __forceinline__ void tma3d(uint32_t dst, const CUtensorMap* m, int c0, int c1, int c2, uint32_t bar) {
  asm volatile("cp.async.bulk.tensor.3d.shared::cluster.global.mbarrier::complete_tx::bytes [%0], [%1, {%3, %4, %5}], [%2];"
               :: "r"(dst), "l"(m), "r"(bar), "r"(c0), "r"(c1), "r"(c2) : "memory");
}
__device__ __forceinline__ void tma2d(uint32_t dst, const CUtensorMap* m, int c0, int c1, uint32_t bar) {
  asm volatile("cp.async.bulk.tensor.2d.shared::cluster.global.mbarrier::complete_tx::bytes [%0], [%1, {%3, %4}], [%2];"
               :: "r"(dst), "l"(m), "r"(bar), "r"(c0), "r"(c1) : "memory");
}
__device__ __forceinline__ void wg_fence() { asm volatile("wgmma.fence.sync.aligned;" ::: "memory"); }
__device__ __forceinline__ void wg_commit() { asm volatile("wgmma.commit_group.sync.aligned;" ::: "memory"); }
template <int N> __device__ __forceinline__ void wg_wait() { asm volatile("wgmma.wait_group.sync.aligned %0;" :: "n"(N) : "memory"); }
template <int SWZ = 1>
__device__ __forceinline__ uint64_t make_desc(uint32_t addr, uint32_t lbo, uint32_t sbo) {
  return (uint64_t)((addr & 0x3FFFF) >> 4) | ((uint64_t)(lbo >> 4) << 16) | ((uint64_t)(sbo >> 4) << 32) | ((uint64_t)SWZ << 62);
}
__device__ __forceinline__ float tanh_fast(float x) { float y; asm("tanh.approx.f32 %0, %1;" : "=f"(y) : "f"(x)); return y; }
__device__ __forceinline__ uint32_t pack_bf16(float lo, float hi) { uint32_t r; asm("cvt.rn.bf16x2.f32 %0, %1, %2;" : "=r"(r) : "f"(hi), "f"(lo)); return r; }
__device__ __forceinline__ uint32_t pack_f16(float lo, float hi) { uint32_t r; asm("cvt.rn.f16x2.f32 %0, %1, %2;" : "=r"(r) : "f"(hi), "f"(lo)); return r; }
__device__ __forceinline__ float f16lo(uint32_t v) { float r; asm("{.reg .b16 l, h; mov.b32 {l, h}, %1; cvt.f32.f16 %0, l;}" : "=f"(r) : "r"(v)); return r; }
__device__ __forceinline__ float f16hi(uint32_t v) { float r; asm("{.reg .b16 l, h; mov.b32 {l, h}, %1; cvt.f32.f16 %0, h;}" : "=f"(r) : "r"(v)); return r; }
__device__ __forceinline__ uint32_t hadd2_bf16(uint32_t a, uint32_t b) { uint32_t r; asm("add.rn.bf16x2 %0, %1, %2;" : "=r"(r) : "r"(a), "r"(b)); return r; }
__device__ __forceinline__ uint32_t movm(uint32_t a) { uint32_t r; asm volatile("movmatrix.sync.aligned.m8n8.trans.b16 %0, %1;" : "=r"(r) : "r"(a)); return r; }
__device__ __forceinline__ void ldsm4t(uint32_t (&r)[4], uint32_t addr) {
  asm volatile("ldmatrix.sync.aligned.m8n8.x4.trans.shared.b16 {%0,%1,%2,%3}, [%4];" : "=r"(r[0]), "=r"(r[1]), "=r"(r[2]), "=r"(r[3]) : "r"(addr) : "memory");
}

__device__ __forceinline__ void wgmma_rs_p128(float (&d)[64], uint32_t a0, uint32_t a1, uint32_t a2, uint32_t a3, uint64_t db, int scale_d) {
  asm volatile("{\n.reg .pred p;\nsetp.ne.b32 p, %69, 0;\n"
    "wgmma.mma_async.sync.aligned.m64n128k16.f32.bf16.bf16 {%0, %1, %2, %3, %4, %5, %6, %7, %8, %9, %10, %11, %12, %13, %14, %15, %16, %17, %18, %19, %20, %21, %22, %23, %24, %25, %26, %27, %28, %29, %30, %31, %32, %33, %34, %35, %36, %37, %38, %39, %40, %41, %42, %43, %44, %45, %46, %47, %48, %49, %50, %51, %52, %53, %54, %55, %56, %57, %58, %59, %60, %61, %62, %63}, {%64, %65, %66, %67}, %68, p, 1, 1, 0;\n}\n"
    : "+f"(d[0]), "+f"(d[1]), "+f"(d[2]), "+f"(d[3]), "+f"(d[4]), "+f"(d[5]), "+f"(d[6]), "+f"(d[7]), "+f"(d[8]), "+f"(d[9]), "+f"(d[10]), "+f"(d[11]), "+f"(d[12]), "+f"(d[13]), "+f"(d[14]), "+f"(d[15]), "+f"(d[16]), "+f"(d[17]), "+f"(d[18]), "+f"(d[19]), "+f"(d[20]), "+f"(d[21]), "+f"(d[22]), "+f"(d[23]), "+f"(d[24]), "+f"(d[25]), "+f"(d[26]), "+f"(d[27]), "+f"(d[28]), "+f"(d[29]), "+f"(d[30]), "+f"(d[31]), "+f"(d[32]), "+f"(d[33]), "+f"(d[34]), "+f"(d[35]), "+f"(d[36]), "+f"(d[37]), "+f"(d[38]), "+f"(d[39]), "+f"(d[40]), "+f"(d[41]), "+f"(d[42]), "+f"(d[43]), "+f"(d[44]), "+f"(d[45]), "+f"(d[46]), "+f"(d[47]), "+f"(d[48]), "+f"(d[49]), "+f"(d[50]), "+f"(d[51]), "+f"(d[52]), "+f"(d[53]), "+f"(d[54]), "+f"(d[55]), "+f"(d[56]), "+f"(d[57]), "+f"(d[58]), "+f"(d[59]), "+f"(d[60]), "+f"(d[61]), "+f"(d[62]), "+f"(d[63])
    : "r"(a0), "r"(a1), "r"(a2), "r"(a3), "l"(db), "r"(scale_d));
}

__device__ __forceinline__ void wgmma_ss_n128_tb(float (&d)[64], uint64_t da, uint64_t db, int scale_d) {
  asm volatile("{\n.reg .pred p;\nsetp.ne.b32 p, %66, 0;\n"
    "wgmma.mma_async.sync.aligned.m64n128k16.f32.bf16.bf16 {%0, %1, %2, %3, %4, %5, %6, %7, %8, %9, %10, %11, %12, %13, %14, %15, %16, %17, %18, %19, %20, %21, %22, %23, %24, %25, %26, %27, %28, %29, %30, %31, %32, %33, %34, %35, %36, %37, %38, %39, %40, %41, %42, %43, %44, %45, %46, %47, %48, %49, %50, %51, %52, %53, %54, %55, %56, %57, %58, %59, %60, %61, %62, %63}, %64, %65, p, 1, 1, 0, 1;\n}\n"
    : "+f"(d[0]), "+f"(d[1]), "+f"(d[2]), "+f"(d[3]), "+f"(d[4]), "+f"(d[5]), "+f"(d[6]), "+f"(d[7]), "+f"(d[8]), "+f"(d[9]), "+f"(d[10]), "+f"(d[11]), "+f"(d[12]), "+f"(d[13]), "+f"(d[14]), "+f"(d[15]), "+f"(d[16]), "+f"(d[17]), "+f"(d[18]), "+f"(d[19]), "+f"(d[20]), "+f"(d[21]), "+f"(d[22]), "+f"(d[23]), "+f"(d[24]), "+f"(d[25]), "+f"(d[26]), "+f"(d[27]), "+f"(d[28]), "+f"(d[29]), "+f"(d[30]), "+f"(d[31]), "+f"(d[32]), "+f"(d[33]), "+f"(d[34]), "+f"(d[35]), "+f"(d[36]), "+f"(d[37]), "+f"(d[38]), "+f"(d[39]), "+f"(d[40]), "+f"(d[41]), "+f"(d[42]), "+f"(d[43]), "+f"(d[44]), "+f"(d[45]), "+f"(d[46]), "+f"(d[47]), "+f"(d[48]), "+f"(d[49]), "+f"(d[50]), "+f"(d[51]), "+f"(d[52]), "+f"(d[53]), "+f"(d[54]), "+f"(d[55]), "+f"(d[56]), "+f"(d[57]), "+f"(d[58]), "+f"(d[59]), "+f"(d[60]), "+f"(d[61]), "+f"(d[62]), "+f"(d[63])
    : "l"(da), "l"(db), "r"(scale_d));
}

template <int NREG> __device__ __forceinline__ void fence_regs(float (&d)[NREG]) {
#pragma unroll
  for (int i = 0; i < NREG; i++) asm volatile("" : "+f"(d[i]) :: "memory");
}

__device__ __forceinline__ uint32_t gate_publish(const float (&t)[8], uint32_t* dst) {
  const float za = t[0] * fmaf(t[2], 0.5f, 0.5f), zb = t[1] * fmaf(t[3], 0.5f, 0.5f);
  const float zc = t[4] * fmaf(t[6], 0.5f, 0.5f), zd = t[5] * fmaf(t[7], 0.5f, 0.5f);
  const uint32_t lo = movm(pack_bf16(za, zb)) & 0xBFFFBFFFu;
  const uint32_t hi = movm(pack_bf16(zc, zd)) & 0xBFFFBFFFu;
  asm volatile("st.relaxed.gpu.global.b32 [%0], %1;" :: "l"(dst), "r"(lo) : "memory");
  asm volatile("st.relaxed.gpu.global.b32 [%0], %1;" :: "l"(dst + 64), "r"(hi) : "memory");
  return hi;
}
__device__ __forceinline__ float tanh_v(float x) { float y; asm volatile("tanh.approx.f32 %0, %1;" : "=f"(y) : "f"(x)); return y; }

__global__ void __cluster_dims__(2, 1, 1) __launch_bounds__(NTHREADS, 1)
wavenet_kernel(const __grid_constant__ CUtensorMap tmX, const __grid_constant__ CUtensorMap tmW,
               const __grid_constant__ CUtensorMap tmWo, const __nv_bfloat16* __restrict__ xg,
               const __nv_bfloat16* __restrict__ wg, __nv_bfloat16* __restrict__ out, uint32_t k32) {
  extern __shared__ uint8_t smem_raw[];
  const uint32_t sbase = (smem_u32(smem_raw) + 1023) & ~1023u;
  const uint32_t bars = sbase + OFF_BAR;
  const uint32_t eo_full = bars;
  const uint32_t wb_full = bars + 24;
  const uint32_t wa_full = bars + 40;
  const uint32_t wbc_empty = bars + 56;
  const uint32_t done_loc = bars + 72;
  const uint32_t done_peer = bars + 104;
  const uint32_t sr_full = bars + 136;
  const uint32_t wo_full = bars + 152;
  const uint32_t w23_full = bars + 184;
  const uint32_t z_full = bars + 200;
  const uint32_t pub = bars + 232;
  const uint32_t zorder = bars + 240;
  const int warp = threadIdx.x >> 5, lane = threadIdx.x & 31;
  const int j = blockIdx.x & 15;
  const int tt = blockIdx.x >> 4;
  const int b = tt >> 2, ti = tt & 3;
  const int u0 = ti * TILE_U;
  const uint32_t rank = j & 1, peer = rank ^ 1;

  TS(0);
  auto load_wbc = [&](int k) {
    const uint32_t dst = sbase + OFF_W + (k & 1) * 5 * W_BYTES;
    mbar_expect_tx(wb_full + 8 * (k & 1), 3 * W_BYTES);
    tma3d(dst + 2 * W_BYTES, &tmW, j * 32, 2 * 512 + k * 64, 0, wb_full + 8 * (k & 1));
    tma3d(dst + 3 * W_BYTES, &tmW, j * 32, 3 * 512 + k * 64, 0, wb_full + 8 * (k & 1));
    tma3d(dst + 4 * W_BYTES, &tmW, j * 32, 4 * 512 + k * 64, 0, wb_full + 8 * (k & 1));
  };
  auto load_wa = [&](int k) {
    const uint32_t dst = sbase + OFF_W + (k & 1) * 5 * W_BYTES;
    mbar_expect_tx(wa_full + 8 * (k & 1), 2 * W_BYTES);
    tma3d(dst, &tmW, j * 32, k * 64, 0, wa_full + 8 * (k & 1));
    tma3d(dst + W_BYTES, &tmW, j * 32, 512 + k * 64, 0, wa_full + 8 * (k & 1));
  };
  if (threadIdx.x == 256) {
    asm volatile("prefetch.tensormap [%0];" :: "l"(&tmW) : "memory");
    asm volatile("prefetch.tensormap [%0];" :: "l"(&tmX) : "memory");
    mbar_init(w23_full, 1); mbar_init(eo_full, 1); mbar_init(wb_full, 1); mbar_init(wa_full, 1);
    asm volatile("fence.mbarrier_init.release.cluster;" ::: "memory");
    mbar_expect_tx(w23_full, 2 * W_BYTES);
    tma3d(sbase + OFF_W + 2 * W_BYTES, &tmW, j * 32, 2 * 512, 0, w23_full);
    tma3d(sbase + OFF_W + 3 * W_BYTES, &tmW, j * 32, 3 * 512, 0, w23_full);
    mbar_expect_tx(eo_full, 2 * ARR_BYTES);
    tma4d(sbase + OFF_EO, &tmX, 0, 0, u0 - 3, b, eo_full);
    tma4d(sbase + OFF_EO + ARR_SLOT, &tmX, 0, 2, u0 - 3, b, eo_full);
    mbar_expect_tx(wb_full, W_BYTES);
    tma3d(sbase + OFF_W + 4 * W_BYTES, &tmW, j * 32, 4 * 512, 0, wb_full);
    load_wa(0);
    for (int i = 1; i < 3; i++) mbar_init(eo_full + 8 * i, 1);
    mbar_init(wb_full + 8, 1); mbar_init(wa_full + 8, 1);
    for (int i = 0; i < 2; i++) { mbar_init(wbc_empty + 8 * i, 4); mbar_init(sr_full + 8 * i, 1); }
    for (int i = 0; i < 8; i++) mbar_init(done_loc + 8 * i, 4);
    for (int i = 0; i < 4; i++) { mbar_init(wo_full + 8 * i, 1); mbar_init(z_full + 8 * i, 1); }
    mbar_init(pub, 8);
    asm volatile("st.shared.b32 [%0], %1;" :: "r"(zorder), "r"(0u) : "memory");
    asm volatile("fence.mbarrier_init.release.cluster;" ::: "memory");
  } else {
  }
  __syncthreads();
  cluster_arrive();

  if (warp >= 8) {
    asm volatile("setmaxnreg.dec.sync.aligned.u32 40;");
    cluster_wait();
    if (warp == 9) {
      const unsigned epoch = *(volatile unsigned*)&g_epoch[blockIdx.x];
      for (int k = 1; k < 8; k++) {
        mbar_wait(wb_full + 8 * (k & 1), (k >> 1) & 1);
        mbar_wait(wa_full + 8 * (k & 1), (k >> 1) & 1);
        mbar_wait(eo_full + 8 * (k % 3), (k / 3) & 1);
        asm volatile("bar.sync 1, 160;" ::: "memory");
      }
      for (int i = 0; i < 4; i++) mbar_wait(wo_full + 8 * i, 0);
      asm volatile("bar.sync 1, 160;" ::: "memory");
      if (lane == 0) g_epoch[blockIdx.x] = epoch + 1;
    } else if (warp == 10) {
      for (int k = 0; k < 8; k++) {
        mbar_wait(eo_full + 8 * (k % 3), (k / 3) & 1);
        if (k >= 2) { mbar_wait(done_loc + 8 * ((k - 2) & 3), ((k - 2) >> 2) & 1); mbar_wait(done_peer + 8 * ((k - 2) & 3), ((k - 2) >> 2) & 1); }
        if (k >= 1 && lane == 0) mbar_expect_tx(sr_full + 8 * (k & 1), ARR_BYTES / 2);
        __syncwarp();
        asm volatile("bar.sync 8, 160;" ::: "memory");
      }
      const int q2 = j >> 2;
      const uint32_t* zq = (const uint32_t*)g_z + (size_t)(tt * 4 + q2) * 32 * 512;
      {
        const unsigned target = 16u * (*(volatile unsigned*)&g_epoch[blockIdx.x] + 1u);
        uint32_t spins = 0, v;
        do { asm volatile("ld.acquire.gpu.global.u32 %0, [%1];" : "=r"(v) : "l"(&g_init[tt * 32]) : "memory"); } while ((int)(v - target) < 0 && ++spins < SPIN_LIMIT);
        asm volatile("fence.proxy.async;" ::: "memory");
      }
      mbar_wait(pub, 0);
      { const uint32_t c0 = (uint32_t)clock(); while ((uint32_t)clock() - c0 < ZDELAY) {} }
      if (lane < 4) {
        mbar_expect_tx(z_full + 8 * lane, 16384);
        bulk_g2s(sbase + ZBUF(lane), zq + lane * 4096, 16384, z_full + 8 * lane);
      }
      __syncwarp();
    } else if (warp == 11) {
      for (int k = 0; k < 8; k++) {
        if (k >= 1) {
          mbar_wait(sr_full + 8 * (k & 1), (k & 1) ? ((k >> 1) & 1) : (((k >> 1) - 1) & 1));
          asm volatile("fence.proxy.async.shared::cta;" ::: "memory");
        }
        asm volatile("bar.sync 2, 288;" ::: "memory");
        if (k == MBOX_K + 1) {
          __threadfence();
          if (lane == 0) asm volatile("red.relaxed.gpu.global.add.u32 [%0], 1;" :: "l"(&g_init[tt * 32]) : "memory");
        }
      }
    } else if (lane == 0) {
      auto load_eo = [&](int k) {
        const uint32_t dst = sbase + OFF_EO + (k % 3) * 2 * ARR_SLOT + rank * ARR_SLOT, bar = eo_full + 8 * (k % 3);
        mbar_expect_tx(bar, 2 * ARR_BYTES);
        tma4d_mc(dst, &tmX, k * 64, 2 * rank, u0 - 3, b, bar, (uint16_t)3);
      };
      const int oq = j & 3;
      auto load_wo = [&](int rb, int half, uint32_t dst) {
        tma2d(dst, &tmWo, oq * 128 + half * 64, rb * 128, wo_full + 8 * rb);
      };
      load_eo(1); load_wbc(1); load_wa(1);
      load_eo(2);
      asm volatile("prefetch.tensormap [%0];" :: "l"(&tmWo) : "memory");
      for (int k = 0; k < 6; k++) {
        mbar_wait(wbc_empty + 8 * (k & 1), (k >> 1) & 1);
        load_wbc(k + 2);
        mbar_wait(done_loc + 8 * (k & 3), (k >> 2) & 1);
        load_wa(k + 2);
        if (k + 3 < 8) { mbar_wait(done_peer + 8 * (k & 3), (k >> 2) & 1); load_eo(k + 3); }
      }
      mbar_expect_tx(wo_full, 32768);
      load_wo(0, 0, sbase + OFF_EO + 4 * ARR_SLOT); load_wo(0, 1, sbase + OFF_EO + 4 * ARR_SLOT + 16384);
      mbar_wait(done_loc + 8 * 2, 1);
      mbar_expect_tx(wo_full + 8, 32768);
      load_wo(1, 0, sbase + OFF_EO); load_wo(1, 1, sbase + OFF_EO + 16384);
      mbar_expect_tx(wo_full + 16, 32768);
      load_wo(2, 0, sbase + OFF_W); load_wo(2, 1, sbase + OFF_W + 16384);
      mbar_expect_tx(wo_full + 24, 32768);
      load_wo(3, 0, sbase + OFF_S);
      mbar_wait(wbc_empty + 8, 1);
      load_wo(3, 1, sbase + OFF_W + 5 * W_BYTES + 2 * W_BYTES);
    }
    __syncwarp();
  } else if (warp >= 4) {
    asm volatile("setmaxnreg.dec.sync.aligned.u32 152;");
    const int tid = threadIdx.x - 128, hw = warp - 4;
    cluster_wait();
    {
      const uint32_t off = hw * (ARR_BYTES / 4) + lane * 16;
      const uint32_t E = sbase + OFF_EO + off, S = sbase + OFF_S + off;
      asm volatile("bar.sync 8, 160;" ::: "memory");
#pragma unroll
      for (int i = 0; i < 8; i++) {
        uint32_t x0, x1, x2, x3, y0, y1, y2, y3;
        asm volatile("ld.shared.v4.b32 {%0,%1,%2,%3}, [%4];" : "=r"(x0), "=r"(x1), "=r"(x2), "=r"(x3) : "r"(E + i * 512));
        asm volatile("ld.shared.v4.b32 {%0,%1,%2,%3}, [%4];" : "=r"(y0), "=r"(y1), "=r"(y2), "=r"(y3) : "r"(E + ARR_SLOT + i * 512));
        asm volatile("st.shared.v4.b32 [%0], {%1,%2,%3,%4};" :: "r"(S + i * 512), "r"(hadd2_bf16(x0, y0)), "r"(hadd2_bf16(x1, y1)), "r"(hadd2_bf16(x2, y2)), "r"(hadd2_bf16(x3, y3)));
      }
      {
        uint32_t mx, my;
        asm volatile("ld.shared.b32 %0, [%1];" : "=r"(mx) : "r"(E - lane * 12 + 4096));
        asm volatile("ld.shared.b32 %0, [%1];" : "=r"(my) : "r"(E - lane * 12 + 4096 + ARR_SLOT));
        asm volatile("st.shared.b32 [%0], %1;" :: "r"(S - lane * 12 + 4096), "r"(hadd2_bf16(mx, my)));
      }
      asm volatile("fence.proxy.async.shared::cta;" ::: "memory");
      asm volatile("bar.arrive 2, 288;" ::: "memory");
    }
    const uint32_t myoff = rank * (ARR_BYTES / 2) + hw * (ARR_BYTES / 8) + lane * 16;
    const uint32_t s_peer = mapa(sbase + OFF_S, peer), sbar_peer = mapa(sr_full, peer);
    for (int k = 1; k < 8; k++) {
      const uint32_t E = sbase + OFF_EO + (k % 3) * 2 * ARR_SLOT + myoff;
      const uint32_t S = sbase + OFF_S + (k & 1) * ARR_SLOT + myoff;
      const uint32_t Sr = s_peer + (k & 1) * ARR_SLOT + myoff;
      const uint32_t sbar_r = sbar_peer + 8 * (k & 1);
      asm volatile("bar.sync 8, 160;" ::: "memory");
      uint32_t X[2][4], Y[2][4], mx = 0, my = 0;
#pragma unroll
      for (int i = 0; i < 5; i++) {
        if (i < 4) {
          asm volatile("bar.sync %0, 256;" :: "r"(4 + i) : "memory");
          asm volatile("ld.shared.v4.b32 {%0,%1,%2,%3}, [%4];" : "=r"(X[i & 1][0]), "=r"(X[i & 1][1]), "=r"(X[i & 1][2]), "=r"(X[i & 1][3]) : "r"(E + i * 512) : "memory");
          asm volatile("ld.shared.v4.b32 {%0,%1,%2,%3}, [%4];" : "=r"(Y[i & 1][0]), "=r"(Y[i & 1][1]), "=r"(Y[i & 1][2]), "=r"(Y[i & 1][3]) : "r"(E + ARR_SLOT + i * 512) : "memory");
          if (i == 0 && lane < 16) {
            asm volatile("ld.shared.b32 %0, [%1];" : "=r"(mx) : "r"(E - lane * 12 + 2048) : "memory");
            asm volatile("ld.shared.b32 %0, [%1];" : "=r"(my) : "r"(E - lane * 12 + 2048 + ARR_SLOT) : "memory");
          }
        }
        if (i >= 1) {
          const int p = (i - 1) & 1;
          const uint32_t z0 = hadd2_bf16(X[p][0], Y[p][0]), z1 = hadd2_bf16(X[p][1], Y[p][1]), z2 = hadd2_bf16(X[p][2], Y[p][2]), z3 = hadd2_bf16(X[p][3], Y[p][3]);
          asm volatile("st.async.weak.shared::cluster.mbarrier::complete_tx::bytes.v4.b32 [%0], {%1,%2,%3,%4}, [%5];" :: "r"(Sr + (i - 1) * 512), "r"(z0), "r"(z1), "r"(z2), "r"(z3), "r"(sbar_r) : "memory");
          asm volatile("st.shared.v4.b32 [%0], {%1,%2,%3,%4};" :: "r"(S + (i - 1) * 512), "r"(z0), "r"(z1), "r"(z2), "r"(z3) : "memory");
          if (i == 1 && lane < 16) {
            const uint32_t mz = hadd2_bf16(mx, my);
            asm volatile("st.async.weak.shared::cluster.mbarrier::complete_tx::bytes.b32 [%0], %1, [%2];" :: "r"(Sr - lane * 12 + 2048), "r"(mz), "r"(sbar_r) : "memory");
            asm volatile("st.shared.b32 [%0], %1;" :: "r"(S - lane * 12 + 2048), "r"(mz) : "memory");
          }
        }
      }
      asm volatile("fence.proxy.async.shared::cta;" ::: "memory");
      asm volatile("bar.arrive 2, 288;" ::: "memory");
      if (k == MBOX_K) {
        uint4* zi = g_z + ((size_t)(tt * 4) * 32 + 2 * j) * 128 + lane + hw * 32 * 128;
#pragma unroll
        for (int i = 0; i < 8; i++)
          asm volatile("st.relaxed.gpu.global.v4.b32 [%0], {%1,%1,%1,%1};" :: "l"(zi + i * 32), "r"(0x40004000u) : "memory");
      }
    }
    {
      uint32_t* zdst = (uint32_t*)g_z + (size_t)(tt * 4) * 32 * 512 + (2 * j + (hw >> 1)) * 512 + (hw & 1) * 32 + lane;
      float tp[8];
#pragma unroll
      for (int p = 0; p <= 8; p++) {
        float t[8];
        if (p < 8) {
          asm volatile("bar.sync %0, 256;" :: "r"(EPI_BAR(p)) : "memory");
          uint32_t v0, v1, v2, v3;
          asm volatile("ld.shared.v4.b32 {%0,%1,%2,%3}, [%4];" : "=r"(v0), "=r"(v1), "=r"(v2), "=r"(v3) : "r"(sbase + YBUF(p) + tid * 16) : "memory");
          const float y[8] = {f16lo(v0), f16hi(v0), f16lo(v1), f16hi(v1), f16lo(v2), f16hi(v2), f16lo(v3), f16hi(v3)};
#pragma unroll
          for (int i = 0; i < 8; i++) t[i] = tanh_v(y[i]);
        }
        if (p >= 1) {
          const int jb = 2 * (p - 1) + 1;
          gate_publish(tp, zdst + (size_t)(jb >> 2) * 32 * 512 + (jb & 3) * 128);
          if ((jb & 3) == 3 && (jb >> 2) == (j >> 2) && lane == 0) mbar_arrive(pub);
        }
        if (p < 8) {
#pragma unroll
          for (int i = 0; i < 8; i++) tp[i] = t[i];
        }
      }
    }
    {
      const int q2 = j >> 2;
      const uint32_t* zq = (const uint32_t*)g_z + (size_t)(tt * 4 + q2) * 32 * 512 + hw * 4096;
      const uint32_t zb = sbase + ZBUF(hw);
      const uint32_t zl = zb + lane * 32 + (lane >> 2) * 4;
      uint32_t ph = 0, spins = 0;
      uint32_t w[16];
      while (true) {
        mbar_wait(z_full + 8 * hw, ph);
#pragma unroll
        for (int i = 0; i < 16; i++) asm volatile("ld.shared.b32 %0, [%1];" : "=r"(w[i]) : "r"(zl + i * 1024) : "memory");
        uint32_t bad = 0;
#pragma unroll
        for (int i = 0; i < 16; i++) bad |= w[i];
        if (!__any_sync(0xffffffffu, (bad & 0x4000u) != 0) || ++spins > SPIN_LIMIT) break;
        ph ^= 1;
        if (lane == 0) {
          mbar_expect_tx(z_full + 8 * hw, 16384);
          bulk_g2s(zb, zq, 16384, z_full + 8 * hw);
        }
      }
      uint32_t slot = 0;
      if (lane == 0) {
        asm volatile("atom.shared.add.u32 %0, [%1], 1;" : "=r"(slot) : "r"(zorder) : "memory");
        asm volatile("st.shared.b32 [%0], %1;" :: "r"(zorder + 4 + 4 * slot), "r"(hw) : "memory");
      }
      slot = __shfl_sync(0xffffffffu, slot, 0);
      asm volatile("bar.arrive %0, 160;" :: "r"(slot == 0 ? 3 : 12 + slot) : "memory");
    }
  } else {
    asm volatile("setmaxnreg.inc.sync.aligned.u32 256;");
    float P0[64], P1[64], P2[64];
    const uint32_t lm_off = ((lane >> 3) & 1) * 4096 + (((lane >> 4) * 8 + (lane & 7)) * 64) + ((warp ^ (((lane & 7) >> 1) & 3)) << 4);
    uint32_t Ra[3][4], Rb[3][4], Sm[2][4];
    mbar_wait(w23_full, 0);
    ldsm4t(Ra[0], sbase + OFF_W + 2 * W_BYTES + lm_off); ldsm4t(Rb[0], sbase + OFF_W + 3 * W_BYTES + lm_off);
    cluster_wait();
    const uint32_t done_rem = mapa(done_peer, peer);
    mbar_wait(wb_full, 0);
    mbar_wait(eo_full, 0);
    TS(1);
    asm volatile("bar.sync 2, 288;" ::: "memory");
    TS(7);
#pragma unroll 1
    for (int k = 0; k < 8; k++) {
      const uint32_t E = sbase + OFF_EO + (k % 3) * 2 * ARR_SLOT;
      const uint32_t W = sbase + OFF_W + (k & 1) * 5 * W_BYTES + lm_off;
      const uint32_t Wn = sbase + OFF_W + ((k + 1) & 1) * 5 * W_BYTES + lm_off;
      const uint64_t dE = make_desc(E, 0, 1024), dO = make_desc(E + ARR_SLOT, 0, 1024);
      const uint64_t dS = make_desc(sbase + OFF_S + (k & 1) * ARR_SLOT, 0, 1024);
#pragma unroll
      for (int gi = 0; gi < 12; gi++) {
        const int type = gi < 8 ? ((gi & 1) ? 2 : 1) : 0;
        const int ks = gi < 8 ? (gi >> 1) : (gi - 8);
        const int ri = gi % 3, si = gi & 1;
        {
          const int gn = (gi + 1) % 12, rn = (gi + 1) % 3;
          const int tn = gn < 8 ? ((gn & 1) ? 2 : 1) : 0, ksn = gn < 8 ? (gn >> 1) : (gn - 8);
          if (gi < 11) {
            const uint32_t base = W + (tn == 0 ? 0 : tn == 1 ? 2 : 4) * W_BYTES + ksn * 1024;
            ldsm4t(Ra[rn], base);
            if (tn != 2) ldsm4t(Rb[rn], base + W_BYTES);
          } else if (k < 7) {
            ldsm4t(Ra[rn], Wn + 2 * W_BYTES); ldsm4t(Rb[rn], Wn + 3 * W_BYTES);
          }
        }
        if (type != 2) {
#pragma unroll
          for (int i = 0; i < 4; i++) Sm[si][i] = hadd2_bf16(Ra[ri][i], Rb[ri][i]);
        }
        const uint64_t sh = (uint64_t)(((type == 0 ? 2 : type == 1 ? 1 : 0) * 256 + ks * 32) >> 4);
        const int sc = (gi == 0) ? (k != 0) : 1;
        wg_fence();
        wgmma_rs_p128(P0, Ra[ri][0], Ra[ri][1], Ra[ri][2], Ra[ri][3], dE + sh, sc);
        if (type != 2) {
          wgmma_rs_p128(P1, Rb[ri][0], Rb[ri][1], Rb[ri][2], Rb[ri][3], dO + sh, sc);
          wgmma_rs_p128(P2, Sm[si][0], Sm[si][1], Sm[si][2], Sm[si][3], dS + sh, sc);
        } else {
          wgmma_rs_p128(P2, Ra[ri][0], Ra[ri][1], Ra[ri][2], Ra[ri][3], dS + sh, 1);
        }
        wg_commit();
        if (TICKS(gi) >= 0 && k < 7) asm volatile("bar.arrive %0, 256;" :: "r"(4 + TICKS(gi)) : "memory");
        if (gi == 5 && k == 0) mbar_wait(wa_full, 0);
        if (gi == 10 && k < 7) asm volatile("bar.sync 1, 160;" ::: "memory");
        if (gi == 11 && k < 7) asm volatile("bar.sync 2, 288;" ::: "memory");
        wg_wait<1>();
        if (gi == 0 && k > 0 && lane == 0) { mbar_arrive(done_loc + 8 * ((k - 1) & 3)); mbar_arrive_remote(done_rem + 8 * ((k - 1) & 3)); }
        if (gi == 8 && lane == 0) mbar_arrive(wbc_empty + 8 * (k & 1));
      }
    }
    wg_wait<0>();
    fence_regs(P0); fence_regs(P1); fence_regs(P2);
    if (lane == 0) mbar_arrive(done_loc + 8 * 3);
    TS(2);
    {
      uint32_t* zdst = (uint32_t*)g_z + (size_t)(tt * 4) * 32 * 512 + (2 * j + (warp >> 1)) * 512 + (warp & 1) * 32 + lane;
      const int qq = lane & 3;
      const int src = (lane & ~3) | ((lane - 1) & 3);
      auto shifted = [&](const int jb, uint32_t& rf, uint32_t& rg) {
        const uint32_t pf = pack_f16(P1[4 * jb + 0], P1[4 * jb + 1]), pg = pack_f16(0.5f * P1[4 * jb + 2], 0.5f * P1[4 * jb + 3]);
        const uint32_t qf = jb > 0 ? pack_f16(P1[4 * jb - 4], P1[4 * jb - 3]) : 0u, qg = jb > 0 ? pack_f16(0.5f * P1[4 * jb - 2], 0.5f * P1[4 * jb - 1]) : 0u;
        rf = __shfl_sync(0xffffffffu, (qq == 3) ? qf : pf, src);
        rg = __shfl_sync(0xffffffffu, (qq == 3) ? qg : pg, src);
      };
      uint32_t rf[2][2], rg[2][2];
      shifted(0, rf[0][0], rg[0][0]); shifted(1, rf[0][1], rg[0][1]);
      float tp[8];
      float ones[2] = {1.0f, 1.0f}, halves[2] = {0.5f, 0.5f};
#pragma unroll
      for (int p = 0; p <= 8; p++) {
        float t[8];
        if (p < 8) {
          if (p < 7) { shifted(2 * p + 2, rf[(p + 1) & 1][0], rg[(p + 1) & 1][0]); shifted(2 * p + 3, rf[(p + 1) & 1][1], rg[(p + 1) & 1][1]); }
          float y[2][8];
          const float one = ones[p & 1], half = halves[p & 1];
#pragma unroll
          for (int h = 1; h >= 0; h--) {
            const int jb = 2 * p + h;
            const uint32_t f = rf[p & 1][h], g = rg[p & 1][h];
            y[h][0] = fmaf(P0[4 * jb + 0], one, f16lo(f)); y[h][1] = fmaf(P0[4 * jb + 1], one, f16hi(f));
            y[h][2] = fmaf(P0[4 * jb + 2], half, f16lo(g)); y[h][3] = fmaf(P0[4 * jb + 3], half, f16hi(g));
            y[h][4] = fmaf(P2[4 * jb + 0], one, -P0[4 * jb + 0]) - P1[4 * jb + 0]; y[h][5] = fmaf(P2[4 * jb + 1], one, -P0[4 * jb + 1]) - P1[4 * jb + 1];
            y[h][6] = fmaf(fmaf(P2[4 * jb + 2], one, -P0[4 * jb + 2]), 0.5f, -0.5f * P1[4 * jb + 2]);
            y[h][7] = fmaf(fmaf(P2[4 * jb + 3], one, -P0[4 * jb + 3]), 0.5f, -0.5f * P1[4 * jb + 3]);
          }
          asm volatile("st.shared.v4.b32 [%0], {%1,%2,%3,%4};" :: "r"(sbase + YBUF(p) + threadIdx.x * 16), "r"(pack_f16(y[1][0], y[1][1])), "r"(pack_f16(y[1][2], y[1][3])),
                       "r"(pack_f16(y[1][4], y[1][5])), "r"(pack_f16(y[1][6], y[1][7])) : "memory");
          asm volatile("bar.arrive %0, 256;" :: "r"(EPI_BAR(p)) : "memory");
#pragma unroll
          for (int i = 0; i < 8; i++) t[i] = tanh_v(y[0][i]);
        }
        if (p >= 1) {
          const int jb = 2 * (p - 1);
          const uint32_t z0 = gate_publish(tp, zdst + (size_t)(jb >> 2) * 32 * 512 + (jb & 3) * 128) >> k32;
          ones[(p + LOOKA) & 1] = __uint_as_float(z0 | 0x3F800000u); halves[(p + LOOKA) & 1] = __uint_as_float(z0 | 0x3F000000u);
          if ((jb & 3) == 2 && (jb >> 2) == (j >> 2) && lane == 0) mbar_arrive(pub);
        }
        if (p < 8) {
#pragma unroll
          for (int i = 0; i < 8; i++) tp[i] = t[i];
        }
      }
    }
    TS(3);
    const int q2 = j >> 2, oq = j & 3;
    float acc2[64];
#define CL(i)
    CL(0);
    asm volatile("bar.sync 1, 160;" ::: "memory");
#pragma unroll
    for (int n = 0; n < 4; n++) {
      asm volatile("bar.sync %0, 160;" :: "r"(ZBAR(n)) : "memory");
      uint32_t bt;
      asm volatile("ld.shared.b32 %0, [%1];" : "=r"(bt) : "r"(zorder + 4 + 4 * n) : "memory");
      const uint64_t dwo = make_desc(sbase + WOBUF(bt), WOLBO(bt), 1024);
      const uint64_t dz = make_desc<0>(sbase + ZBUF(bt), 128, 256);
      CL(1 + n);
      wg_fence();
#pragma unroll
      for (int i = 0; i < 8; i++)
        wgmma_ss_n128_tb(acc2, dz + (uint64_t)(i * (2048 >> 4)), dwo + (uint64_t)(i * (2048 >> 4)), (n | i) != 0);
      wg_commit();
    }
    CL(5); CL(6);
    wg_wait<0>();
    fence_regs(acc2);
    CL(7);
    TS(5);
    {
      const int r = lane >> 2, qq = lane & 3, e = qq & 1;
      const int tl = q2 * 64 + warp * 16 + 4 * (r >> 1) + (r & 1) - 4;
      const int tbase = ti * (4 * TILE_U);
#pragma unroll
      for (int h = 0; h < 2; h++) {
        const int tloc = tl + 2 * h, tg = tbase + tloc;
        const bool ok = tloc >= 0 && tg < T_LEN;
        __nv_bfloat16* obase = out + ((size_t)b * T_LEN + tg) * 512 + oq * 128;
#pragma unroll
        for (int i = 0; i < 8; i++) {
          const uint32_t u0_ = pack_bf16(acc2[8 * i + 2 * h], acc2[8 * i + 2 * h + 1]);
          const uint32_t u1_ = pack_bf16(acc2[8 * i + 4 + 2 * h], acc2[8 * i + 4 + 2 * h + 1]);
          const uint32_t snd = e ? u0_ : u1_;
          const uint32_t rcv = __shfl_xor_sync(0xffffffffu, snd, 1);
          const uint32_t lo = e ? rcv : u0_, hi = e ? u1_ : rcv;
          const int col = 16 * i + (e ? 8 + 2 * (qq - 1) : 2 * qq);
          if (ok) asm volatile("st.global.v2.b32 [%0], {%1,%2};" :: "l"(obase + col), "r"(lo), "r"(hi) : "memory");
        }
      }
    }
    TS(6);
  }
  cluster_arrive_rel();
  cluster_wait();
}

#define CK(x) (x)
typedef CUresult (*EncFn)(CUtensorMap*, CUtensorMapDataType, cuuint32_t, void*, const cuuint64_t*, const cuuint64_t*,
                          const cuuint32_t*, const cuuint32_t*, CUtensorMapInterleave, CUtensorMapSwizzle,
                          CUtensorMapL2promotion, CUtensorMapFloatOOBfill);

}

extern "C" void kernel_launch(void* const* d_in, const int* in_sizes, int n_in, void* d_out, int out_size) {
  static EncFn enc = nullptr;
  if (!enc) {
    void* fn = nullptr; cudaDriverEntryPointQueryResult qr;
    cudaGetDriverEntryPoint("cuTensorMapEncodeTiled", &fn, cudaEnableDefault, &qr);
    enc = (EncFn)fn;
    cudaFuncSetAttribute(wavenet_kernel, cudaFuncAttributeMaxDynamicSharedMemorySize, SMEM_BYTES);
  }
  CUtensorMap tmX, tmW, tmWo;
  {
    cuuint64_t dims[4] = {512, 4, 250, 2}; cuuint64_t strides[3] = {1024, 4096, 1024000}; cuuint32_t box[4] = {64, 2, 66, 1}; cuuint32_t es[4] = {1, 1, 1, 1};
    CK(enc(&tmX, CU_TENSOR_MAP_DATA_TYPE_BFLOAT16, 4, d_in[0], dims, strides, box, es, CU_TENSOR_MAP_INTERLEAVE_NONE,
        CU_TENSOR_MAP_SWIZZLE_128B, CU_TENSOR_MAP_L2_PROMOTION_L2_128B, CU_TENSOR_MAP_FLOAT_OOB_FILL_NONE));
  }
  {
    cuuint64_t dims[3] = {512, 2560, 2}; cuuint64_t strides[2] = {2048, 1024}; cuuint32_t box[3] = {32, 64, 2}; cuuint32_t es[3] = {1, 1, 1};
    CK(enc(&tmW, CU_TENSOR_MAP_DATA_TYPE_BFLOAT16, 3, d_in[1], dims, strides, box, es, CU_TENSOR_MAP_INTERLEAVE_NONE,
        CU_TENSOR_MAP_SWIZZLE_64B, CU_TENSOR_MAP_L2_PROMOTION_L2_128B, CU_TENSOR_MAP_FLOAT_OOB_FILL_NONE));
  }
  {
    cuuint64_t dims[2] = {512, 512}; cuuint64_t strides[1] = {1024}; cuuint32_t box[2] = {64, 128}; cuuint32_t es[2] = {1, 1};
    CK(enc(&tmWo, CU_TENSOR_MAP_DATA_TYPE_BFLOAT16, 2, d_in[2], dims, strides, box, es, CU_TENSOR_MAP_INTERLEAVE_NONE,
        CU_TENSOR_MAP_SWIZZLE_128B, CU_TENSOR_MAP_L2_PROMOTION_L2_128B, CU_TENSOR_MAP_FLOAT_OOB_FILL_NONE));
  }
  wavenet_kernel<<<128, NTHREADS, SMEM_BYTES, cudaStreamPerThread>>>(tmX, tmW, tmWo, (const __nv_bfloat16*)d_in[0], (const __nv_bfloat16*)d_in[1], (__nv_bfloat16*)d_out, 32u);
}
```

```cpp
#include <cuda_runtime.h>
#include <cuda_bf16.h>
#include <cuda.h>
#include <stdint.h>

namespace {

constexpr int T_LEN = 1000;
constexpr int TILE_U = 63;
constexpr int ARR_BYTES = 132 * 128;
constexpr int ARR_SLOT = 17408;
constexpr int W_BYTES = 64 * 128;
constexpr int OFF_EO = 0;
constexpr int OFF_S = 3 * 2 * ARR_SLOT;
constexpr int OFF_W = OFF_S + 2 * ARR_SLOT;
constexpr int OFF_BAR = OFF_W + 2 * 5 * W_BYTES;
constexpr int SMEM_BYTES = OFF_BAR + 512 + 1024;
constexpr int NTHREADS = 512;
constexpr uint32_t SPIN_LIMIT = 1u << 16;
constexpr uint32_t ZSTAG = 140;
#define VG 4
#define NHALF 8
#define TICK0 0
#define MINI_AT 5
constexpr uint32_t ZDELAY2 = 50;
#define ZBUF(b) ((b) == 0 ? OFF_EO + 2 * ARR_SLOT : (b) == 1 ? OFF_EO + 2 * ARR_SLOT + 16384 : (b) == 2 ? OFF_S + ARR_SLOT : OFF_W + 5 * W_BYTES)
#define PBUF(g) (OFF_S + ARR_SLOT + (g) * 1024)
#define OFF_Y (OFF_EO + 2 * ARR_SLOT)
#define VBAR 3
#define LBAR(b) ((b) == 0 ? 2 : (b) == 1 ? 8 : 12 + (b))
#define WOBUF(b) ((b) == 0 ? OFF_EO + 4 * ARR_SLOT : (b) == 1 ? OFF_EO : (b) == 2 ? OFF_W : OFF_S)
#define WOLBO(b) ((b) == 3 ? OFF_W + 7 * W_BYTES - OFF_S : 16384)
#define EPI_BAR(p) ((p) < 4 ? 4 + (p) : 5 + (p))

__device__ uint4 g_z[8 * 4 * 32 * 128];
__device__ unsigned g_epoch[128];
__device__ unsigned g_init[8 * 32];

__device__ __forceinline__ uint32_t smem_u32(const void* p) { return (uint32_t)__cvta_generic_to_shared(p); }
__device__ __forceinline__ void mbar_init(uint32_t bar, uint32_t cnt) { asm volatile("mbarrier.init.shared::cta.b64 [%0], %1;" :: "r"(bar), "r"(cnt)); }
__device__ __forceinline__ void mbar_expect_tx(uint32_t bar, uint32_t bytes) { asm volatile("mbarrier.arrive.expect_tx.shared::cta.b64 _, [%0], %1;" :: "r"(bar), "r"(bytes) : "memory"); }
__device__ __forceinline__ void mbar_arrive(uint32_t bar) { asm volatile("mbarrier.arrive.shared::cta.b64 _, [%0];" :: "r"(bar) : "memory"); }
__device__ __forceinline__ void mbar_wait(uint32_t bar, uint32_t parity) {
  asm volatile("{\n.reg .pred p;\nWAIT_%=:\nmbarrier.try_wait.parity.shared::cta.b64 p, [%0], %1;\n@p bra DONE_%=;\nbra WAIT_%=;\nDONE_%=:\n}" :: "r"(bar), "r"(parity) : "memory");
}
__device__ __forceinline__ uint32_t mapa(uint32_t addr, uint32_t rank) { uint32_t r; asm("mapa.shared::cluster.u32 %0, %1, %2;" : "=r"(r) : "r"(addr), "r"(rank)); return r; }
__device__ __forceinline__ void mbar_arrive_remote(uint32_t bar_cluster_addr) { asm volatile("mbarrier.arrive.shared::cluster.b64 _, [%0];" :: "r"(bar_cluster_addr) : "memory"); }
__device__ __forceinline__ void bulk_g2s(uint32_t dst, const void* src, uint32_t bytes, uint32_t bar) {
  asm volatile("cp.async.bulk.shared::cluster.global.mbarrier::complete_tx::bytes [%0], [%1], %2, [%3];" :: "r"(dst), "l"(src), "r"(bytes), "r"(bar) : "memory");
}
__device__ __forceinline__ void tma4d_mc(uint32_t dst, const CUtensorMap* m, int c0, int c1, int c2, int c3, uint32_t bar, uint16_t mask) {
  asm volatile("cp.async.bulk.tensor.4d.shared::cluster.global.mbarrier::complete_tx::bytes.multicast::cluster [%0], [%1, {%3, %4, %5, %6}], [%2], %7;"
               :: "r"(dst), "l"(m), "r"(bar), "r"(c0), "r"(c1), "r"(c2), "r"(c3), "h"(mask) : "memory");
}
__device__ __forceinline__ void cluster_arrive() { asm volatile("barrier.cluster.arrive.relaxed.aligned;" ::: "memory"); }
__device__ __forceinline__ void cluster_wait() { asm volatile("barrier.cluster.wait.acquire.aligned;" ::: "memory"); }
__device__ __forceinline__ void tma4d(uint32_t dst, const CUtensorMap* m, int c0, int c1, int c2, int c3, uint32_t bar) {
  asm volatile("cp.async.bulk.tensor.4d.shared::cluster.global.mbarrier::complete_tx::bytes [%0], [%1, {%3, %4, %5, %6}], [%2];"
               :: "r"(dst), "l"(m), "r"(bar), "r"(c0), "r"(c1), "r"(c2), "r"(c3) : "memory");
}
__device__ __forceinline__ void tma3d(uint32_t dst, const CUtensorMap* m, int c0, int c1, int c2, uint32_t bar) {
  asm volatile("cp.async.bulk.tensor.3d.shared::cluster.global.mbarrier::complete_tx::bytes [%0], [%1, {%3, %4, %5}], [%2];"
               :: "r"(dst), "l"(m), "r"(bar), "r"(c0), "r"(c1), "r"(c2) : "memory");
}
__device__ __forceinline__ void tma2d(uint32_t dst, const CUtensorMap* m, int c0, int c1, uint32_t bar) {
  asm volatile("cp.async.bulk.tensor.2d.shared::cluster.global.mbarrier::complete_tx::bytes [%0], [%1, {%3, %4}], [%2];"
               :: "r"(dst), "l"(m), "r"(bar), "r"(c0), "r"(c1) : "memory");
}
__device__ __forceinline__ void wg_fence() { asm volatile("wgmma.fence.sync.aligned;" ::: "memory"); }
__device__ __forceinline__ void wg_commit() { asm volatile("wgmma.commit_group.sync.aligned;" ::: "memory"); }
template <int N> __device__ __forceinline__ void wg_wait() { asm volatile("wgmma.wait_group.sync.aligned %0;" :: "n"(N) : "memory"); }
template <int SWZ = 1>
__device__ __forceinline__ uint64_t make_desc(uint32_t addr, uint32_t lbo, uint32_t sbo) {
  return (uint64_t)((addr & 0x3FFFF) >> 4) | ((uint64_t)(lbo >> 4) << 16) | ((uint64_t)(sbo >> 4) << 32) | ((uint64_t)SWZ << 62);
}
__device__ __forceinline__ float tanh_fast(float x) { float y; asm("tanh.approx.f32 %0, %1;" : "=f"(y) : "f"(x)); return y; }
__device__ __forceinline__ uint32_t pack_bf16(float lo, float hi) { uint32_t r; asm("cvt.rn.bf16x2.f32 %0, %1, %2;" : "=r"(r) : "f"(hi), "f"(lo)); return r; }
__device__ __forceinline__ float bf16lo(uint32_t v) { return __uint_as_float(v << 16); }
__device__ __forceinline__ float bf16hi(uint32_t v) { return __uint_as_float(v & 0xFFFF0000u); }
__device__ __forceinline__ uint32_t hhalf2_bf16(uint32_t a) { uint32_t r; asm("mul.rn.bf16x2 %0, %1, %2;" : "=r"(r) : "r"(a), "r"(0x3F003F00u)); return r; }
__device__ __forceinline__ uint32_t hadd2_bf16(uint32_t a, uint32_t b) { uint32_t r; asm("add.rn.bf16x2 %0, %1, %2;" : "=r"(r) : "r"(a), "r"(b)); return r; }
__device__ __forceinline__ uint32_t movm(uint32_t a) { uint32_t r; asm volatile("movmatrix.sync.aligned.m8n8.trans.b16 %0, %1;" : "=r"(r) : "r"(a)); return r; }
__device__ __forceinline__ void ldsm4t(uint32_t (&r)[4], uint32_t addr) {
  asm volatile("ldmatrix.sync.aligned.m8n8.x4.trans.shared.b16 {%0,%1,%2,%3}, [%4];" : "=r"(r[0]), "=r"(r[1]), "=r"(r[2]), "=r"(r[3]) : "r"(addr) : "memory");
}

__device__ __forceinline__ void wgmma_rs_p128(float (&d)[64], uint32_t a0, uint32_t a1, uint32_t a2, uint32_t a3, uint64_t db, int scale_d) {
  asm volatile("{\n.reg .pred p;\nsetp.ne.b32 p, %69, 0;\n"
    "wgmma.mma_async.sync.aligned.m64n128k16.f32.bf16.bf16 {%0, %1, %2, %3, %4, %5, %6, %7, %8, %9, %10, %11, %12, %13, %14, %15, %16, %17, %18, %19, %20, %21, %22, %23, %24, %25, %26, %27, %28, %29, %30, %31, %32, %33, %34, %35, %36, %37, %38, %39, %40, %41, %42, %43, %44, %45, %46, %47, %48, %49, %50, %51, %52, %53, %54, %55, %56, %57, %58, %59, %60, %61, %62, %63}, {%64, %65, %66, %67}, %68, p, 1, 1, 0;\n}\n"
    : "+f"(d[0]), "+f"(d[1]), "+f"(d[2]), "+f"(d[3]), "+f"(d[4]), "+f"(d[5]), "+f"(d[6]), "+f"(d[7]), "+f"(d[8]), "+f"(d[9]), "+f"(d[10]), "+f"(d[11]), "+f"(d[12]), "+f"(d[13]), "+f"(d[14]), "+f"(d[15]), "+f"(d[16]), "+f"(d[17]), "+f"(d[18]), "+f"(d[19]), "+f"(d[20]), "+f"(d[21]), "+f"(d[22]), "+f"(d[23]), "+f"(d[24]), "+f"(d[25]), "+f"(d[26]), "+f"(d[27]), "+f"(d[28]), "+f"(d[29]), "+f"(d[30]), "+f"(d[31]), "+f"(d[32]), "+f"(d[33]), "+f"(d[34]), "+f"(d[35]), "+f"(d[36]), "+f"(d[37]), "+f"(d[38]), "+f"(d[39]), "+f"(d[40]), "+f"(d[41]), "+f"(d[42]), "+f"(d[43]), "+f"(d[44]), "+f"(d[45]), "+f"(d[46]), "+f"(d[47]), "+f"(d[48]), "+f"(d[49]), "+f"(d[50]), "+f"(d[51]), "+f"(d[52]), "+f"(d[53]), "+f"(d[54]), "+f"(d[55]), "+f"(d[56]), "+f"(d[57]), "+f"(d[58]), "+f"(d[59]), "+f"(d[60]), "+f"(d[61]), "+f"(d[62]), "+f"(d[63])
    : "r"(a0), "r"(a1), "r"(a2), "r"(a3), "l"(db), "r"(scale_d));
}

__device__ __forceinline__ void wgmma_ss_n128_tb(float (&d)[64], uint64_t da, uint64_t db, int scale_d) {
  asm volatile("{\n.reg .pred p;\nsetp.ne.b32 p, %66, 0;\n"
    "wgmma.mma_async.sync.aligned.m64n128k16.f32.bf16.bf16 {%0, %1, %2, %3, %4, %5, %6, %7, %8, %9, %10, %11, %12, %13, %14, %15, %16, %17, %18, %19, %20, %21, %22, %23, %24, %25, %26, %27, %28, %29, %30, %31, %32, %33, %34, %35, %36, %37, %38, %39, %40, %41, %42, %43, %44, %45, %46, %47, %48, %49, %50, %51, %52, %53, %54, %55, %56, %57, %58, %59, %60, %61, %62, %63}, %64, %65, p, 1, 1, 0, 1;\n}\n"
    : "+f"(d[0]), "+f"(d[1]), "+f"(d[2]), "+f"(d[3]), "+f"(d[4]), "+f"(d[5]), "+f"(d[6]), "+f"(d[7]), "+f"(d[8]), "+f"(d[9]), "+f"(d[10]), "+f"(d[11]), "+f"(d[12]), "+f"(d[13]), "+f"(d[14]), "+f"(d[15]), "+f"(d[16]), "+f"(d[17]), "+f"(d[18]), "+f"(d[19]), "+f"(d[20]), "+f"(d[21]), "+f"(d[22]), "+f"(d[23]), "+f"(d[24]), "+f"(d[25]), "+f"(d[26]), "+f"(d[27]), "+f"(d[28]), "+f"(d[29]), "+f"(d[30]), "+f"(d[31]), "+f"(d[32]), "+f"(d[33]), "+f"(d[34]), "+f"(d[35]), "+f"(d[36]), "+f"(d[37]), "+f"(d[38]), "+f"(d[39]), "+f"(d[40]), "+f"(d[41]), "+f"(d[42]), "+f"(d[43]), "+f"(d[44]), "+f"(d[45]), "+f"(d[46]), "+f"(d[47]), "+f"(d[48]), "+f"(d[49]), "+f"(d[50]), "+f"(d[51]), "+f"(d[52]), "+f"(d[53]), "+f"(d[54]), "+f"(d[55]), "+f"(d[56]), "+f"(d[57]), "+f"(d[58]), "+f"(d[59]), "+f"(d[60]), "+f"(d[61]), "+f"(d[62]), "+f"(d[63])
    : "l"(da), "l"(db), "r"(scale_d));
}

template <int NREG> __device__ __forceinline__ void fence_regs(float (&d)[NREG]) {
#pragma unroll
  for (int i = 0; i < NREG; i++) asm volatile("" : "+f"(d[i]) :: "memory");
}

__device__ __forceinline__ uint32_t gate_publish(const float (&t)[8], uint32_t* dst) {
  const float za = t[0] * fmaf(t[2], 0.5f, 0.5f), zb = t[1] * fmaf(t[3], 0.5f, 0.5f);
  const float zc = t[4] * fmaf(t[6], 0.5f, 0.5f), zd = t[5] * fmaf(t[7], 0.5f, 0.5f);
  const uint32_t lo = movm(pack_bf16(za, zb)) & 0xBFFFBFFFu;
  const uint32_t hi = movm(pack_bf16(zc, zd)) & 0xBFFFBFFFu;
  asm volatile("st.relaxed.gpu.global.b32 [%0], %1;" :: "l"(dst), "r"(lo) : "memory");
  asm volatile("st.relaxed.gpu.global.b32 [%0], %1;" :: "l"(dst + 64), "r"(hi) : "memory");
  return hi;
}

__device__ __forceinline__ void check_batch(uint32_t zb, uint32_t zf, uint32_t flags, const int bt, const int lane) {
  const uint32_t zl = zb + lane * 32 + (lane >> 2) * 4;
  uint32_t ph = 0, spins = 0;
  bool mine = true;
  while (true) {
    if (mine) {
      mbar_wait(zf, ph);
    }
    asm volatile("bar.arrive %0, 160;" :: "r"(LBAR(bt)) : "memory");
    if (mine) {
      uint32_t w[16];
#pragma unroll
      for (int i = 0; i < 16; i++) asm volatile("ld.shared.b32 %0, [%1];" : "=r"(w[i]) : "r"(zl + i * 1024) : "memory");
      uint32_t bad = 0;
#pragma unroll
      for (int i = 0; i < 16; i++) bad |= w[i];
      if (__any_sync(0xffffffffu, (bad & 0x4000u) != 0) && lane == 0) asm volatile("red.shared.or.b32 [%0], %1;" :: "r"(flags), "r"(1u << bt) : "memory");
    }
    asm volatile("bar.sync %0, 256;" :: "r"(VBAR) : "memory");
    uint32_t m;
    asm volatile("ld.volatile.shared.b32 %0, [%1];" : "=r"(m) : "r"(flags) : "memory");
    if (m == 0 || ++spins > SPIN_LIMIT) break;
    asm volatile("bar.sync %0, 256;" :: "r"(VBAR) : "memory");
    mine = (m >> bt) & 1;
    if (mine) ph ^= 1;
  }
}

__device__ __forceinline__ void s0_slice(uint32_t sbase, int part, int lane) {
  const uint32_t off = part * (ARR_BYTES / 8) + lane * 16;
  const uint32_t E = sbase + OFF_EO + off, S = sbase + OFF_S + off;
  asm volatile("bar.sync 8, 288;" ::: "memory");
#pragma unroll
  for (int i = 0; i < 4; i++) {
    uint32_t x0, x1, x2, x3, y0, y1, y2, y3;
    asm volatile("ld.shared.v4.b32 {%0,%1,%2,%3}, [%4];" : "=r"(x0), "=r"(x1), "=r"(x2), "=r"(x3) : "r"(E + i * 512));
    asm volatile("ld.shared.v4.b32 {%0,%1,%2,%3}, [%4];" : "=r"(y0), "=r"(y1), "=r"(y2), "=r"(y3) : "r"(E + ARR_SLOT + i * 512));
    asm volatile("st.shared.v4.b32 [%0], {%1,%2,%3,%4};" :: "r"(S + i * 512), "r"(hadd2_bf16(x0, y0)), "r"(hadd2_bf16(x1, y1)), "r"(hadd2_bf16(x2, y2)), "r"(hadd2_bf16(x3, y3)));
  }
  if (lane < 16) {
    uint32_t mx, my;
    asm volatile("ld.shared.b32 %0, [%1];" : "=r"(mx) : "r"(E - lane * 12 + 2048));
    asm volatile("ld.shared.b32 %0, [%1];" : "=r"(my) : "r"(E - lane * 12 + 2048 + ARR_SLOT));
    asm volatile("st.shared.b32 [%0], %1;" :: "r"(S - lane * 12 + 2048), "r"(hadd2_bf16(mx, my)));
  }
  asm volatile("fence.proxy.async.shared::cta;" ::: "memory");
  asm volatile("bar.arrive 2, 416;" ::: "memory");
}

template <int FIRST, int STRIDE, int END, int BARCNT>
__device__ __forceinline__ void activation_stream(uint32_t sbase, int tid, uint32_t* zdst, uint32_t pub, uint32_t qpub, int q2, int lane) {
  constexpr int NG = (END - FIRST + STRIDE - 1) / STRIDE;
  uint32_t ybuf = sbase + OFF_Y + tid * 16;
  uint32_t pbase = sbase + PBUF(0) + ((lane & 3) == 0 ? (tid + 3) * 8 - 1024 : (tid - 1) * 8);
  asm volatile("" : "+r"(pbase), "+r"(ybuf), "+l"(zdst));
  float tp[8];
  uint32_t v[4], s0, s1;
  auto fetch = [&](const int jb) {
    if (STRIDE == 2 || (jb & 1) == 0) asm volatile("bar.sync %0, %1;" :: "r"(EPI_BAR(jb >> 1)), "n"(BARCNT) : "memory");
    asm volatile("ld.shared.v4.b32 {%0,%1,%2,%3}, [%4];" : "=r"(v[0]), "=r"(v[1]), "=r"(v[2]), "=r"(v[3]) : "r"(ybuf + jb * 2048) : "memory");
    asm volatile("ld.shared.v2.b32 {%0,%1}, [%2];" : "=r"(s0), "=r"(s1) : "r"(pbase + jb * 1024) : "memory");
  };
  fetch(FIRST);
#pragma unroll
  for (int p = 0; p <= NG; p++) {
    float t[8];
    if (p < NG) {
      const uint32_t y0f = hadd2_bf16(v[0], s0), y0g = hhalf2_bf16(hadd2_bf16(v[1], s1)), y1f = v[2], y1g = hhalf2_bf16(v[3]);
      const float y[8] = {bf16lo(y0f), bf16hi(y0f), bf16lo(y0g), bf16hi(y0g), bf16lo(y1f), bf16hi(y1f), bf16lo(y1g), bf16hi(y1g)};
      if (p + 1 < NG) fetch(FIRST + STRIDE * (p + 1));
#pragma unroll
      for (int i = 0; i < 8; i++) t[i] = tanh_fast(y[i]);
    }
    if (p >= 1) {
      const int jb = FIRST + STRIDE * (p - 1);
      gate_publish(tp, zdst + (size_t)(jb >> 2) * 32 * 512 + (jb & 3) * 128);
      if ((STRIDE == 2 ? (jb & 2) != 0 : (jb & 3) == 3) && (jb >> 2) == q2 && lane == 0) mbar_arrive(qpub);
    }
    if (p < NG) {
#pragma unroll
      for (int i = 0; i < 8; i++) tp[i] = t[i];
    }
  }
  if (lane == 0) mbar_arrive(pub);
}

__global__ void __cluster_dims__(2, 1, 1) __launch_bounds__(NTHREADS, 1)
wavenet_kernel(const __grid_constant__ CUtensorMap tmX, const __grid_constant__ CUtensorMap tmW,
               const __grid_constant__ CUtensorMap tmWo, __nv_bfloat16* __restrict__ out) {
  extern __shared__ uint8_t smem_raw[];
  const uint32_t sbase = (smem_u32(smem_raw) + 1023) & ~1023u;
  const uint32_t bars = sbase + OFF_BAR;
  const uint32_t eo_full = bars;
  const uint32_t wb_full = bars + 24;
  const uint32_t wa_full = bars + 40;
  const uint32_t wbc_empty = bars + 56;
  const uint32_t done_loc = bars + 72;
  const uint32_t done_peer = bars + 104;
  const uint32_t sr_full = bars + 136;
  const uint32_t wo_full = bars + 152;
  const uint32_t w23_full = bars + 184;
  const uint32_t zero_word = bars + 192;
  const uint32_t z_full = bars + 200;
  const uint32_t qpub = bars + 232;
  const uint32_t pub = bars + 264;
  const uint32_t zorder = bars + 280;
  const int warp = threadIdx.x >> 5, lane = threadIdx.x & 31;
  const int j = blockIdx.x & 15;
  const int tt = blockIdx.x >> 4;
  const int b = tt >> 2, ti = tt & 3;
  const int u0 = ti * TILE_U;
  const uint32_t rank = j & 1, peer = rank ^ 1;
  auto load_wbc = [&](int k) {
    const uint32_t dst = sbase + OFF_W + (k & 1) * 5 * W_BYTES;
    mbar_expect_tx(wb_full + 8 * (k & 1), 3 * W_BYTES);
    tma3d(dst + 2 * W_BYTES, &tmW, j * 32, 2 * 512 + k * 64, 0, wb_full + 8 * (k & 1));
    tma3d(dst + 3 * W_BYTES, &tmW, j * 32, 3 * 512 + k * 64, 0, wb_full + 8 * (k & 1));
    tma3d(dst + 4 * W_BYTES, &tmW, j * 32, 4 * 512 + k * 64, 0, wb_full + 8 * (k & 1));
  };
  auto load_wa = [&](int k) {
    const uint32_t dst = sbase + OFF_W + (k & 1) * 5 * W_BYTES;
    mbar_expect_tx(wa_full + 8 * (k & 1), 2 * W_BYTES);
    tma3d(dst, &tmW, j * 32, k * 64, 0, wa_full + 8 * (k & 1));
    tma3d(dst + W_BYTES, &tmW, j * 32, 512 + k * 64, 0, wa_full + 8 * (k & 1));
  };
  if (threadIdx.x == 256) {
    asm volatile("prefetch.tensormap [%0];" :: "l"(&tmW) : "memory");
    asm volatile("prefetch.tensormap [%0];" :: "l"(&tmX) : "memory");
    mbar_init(w23_full, 1); mbar_init(wb_full, 1); mbar_init(wa_full, 1);
    for (int i = 0; i < 3; i++) mbar_init(eo_full + 8 * i, 1);
    asm volatile("fence.mbarrier_init.release.cluster;" ::: "memory");
    mbar_expect_tx(eo_full, 2 * ARR_BYTES);
    tma4d(sbase + OFF_EO, &tmX, 0, 0, u0 - 3, b, eo_full);
    tma4d(sbase + OFF_EO + ARR_SLOT, &tmX, 0, 2, u0 - 3, b, eo_full);
    mbar_expect_tx(w23_full, 2 * W_BYTES);
    tma3d(sbase + OFF_W + 2 * W_BYTES, &tmW, j * 32, 2 * 512, 0, w23_full);
    tma3d(sbase + OFF_W + 3 * W_BYTES, &tmW, j * 32, 3 * 512, 0, w23_full);
    mbar_expect_tx(wb_full, W_BYTES);
    tma3d(sbase + OFF_W + 4 * W_BYTES, &tmW, j * 32, 4 * 512, 0, wb_full);
    mbar_init(wb_full + 8, 1); mbar_init(wa_full + 8, 1);
    for (int i = 0; i < 2; i++) { mbar_init(wbc_empty + 8 * i, 4); mbar_init(sr_full + 8 * i, 1); }
    for (int i = 0; i < 8; i++) mbar_init(done_loc + 8 * i, 4);
    for (int i = 0; i < 4; i++) { mbar_init(wo_full + 8 * i, 1); mbar_init(z_full + 8 * i, 1); }
    mbar_init(pub, 12);
    mbar_init(qpub, ((j >> 2) * 4 < VG) ? 4 : 8);
    asm volatile("st.shared.b32 [%0], %1;" :: "r"(zorder), "r"(0u) : "memory");
    asm volatile("st.shared.b32 [%0], %1;" :: "r"(zorder + 8), "r"(0u) : "memory");
    asm volatile("st.shared.b32 [%0], %1;" :: "r"(zero_word), "r"(0u) : "memory");
    asm volatile("fence.mbarrier_init.release.cluster;" ::: "memory");
    asm volatile("fence.acq_rel.cta;" ::: "memory");
  }
  __syncwarp();
  cluster_arrive();

  if (warp >= 12) {
    asm volatile("setmaxnreg.dec.sync.aligned.u32 56;");
    const int pw = warp - 12;
    const unsigned epoch = *(volatile unsigned*)&g_epoch[blockIdx.x];
    cluster_wait();
    s0_slice(sbase, 4 + pw, lane);
    mbar_wait(done_loc + 8 * 2, 0);
    mbar_wait(done_loc + 8 * 2, 1);
    {
      const unsigned target = 16u * (epoch + 1u);
      uint32_t spins = 0, v;
      do { asm volatile("ld.acquire.gpu.global.u32 %0, [%1];" : "=r"(v) : "l"(&g_init[tt * 32]) : "memory"); } while ((int)(v - target) < 0 && ++spins < SPIN_LIMIT);
      asm volatile("fence.proxy.async;" ::: "memory");
    }
    {
      uint32_t* zdst = (uint32_t*)g_z + (size_t)(tt * 4) * 32 * 512 + (2 * j + (pw >> 1)) * 512 + (pw & 1) * 32 + lane;
      activation_stream<0, 1, VG, 256>(sbase, threadIdx.x - 384, zdst, pub, qpub, j >> 2, lane);
    }
    {
      const int q2 = j >> 2;
      const uint32_t* zq = (const uint32_t*)g_z + (size_t)(tt * 4 + q2) * 32 * 512;
      mbar_wait(qpub, 0);
      if (q2 >= 2) { const uint32_t c0 = (uint32_t)clock(); while ((uint32_t)clock() - c0 < ZDELAY2 + pw * ZSTAG) {} }
      else __nanosleep(40 + 60 * pw);
      bool go = false;
      {
        const uint32_t* src = zq + (size_t)(2 * (lane >> 1) + 1) * 512 + (2 * (2 + (lane & 1)) + 1) * 64 + 32;
        uint32_t spins = 0;
        while (true) {
          uint32_t v, g;
          asm volatile("ld.relaxed.gpu.global.b32 %0, [%1];" : "=r"(v) : "l"(src) : "memory");
          const bool ready = __all_sync(0xffffffffu, (v & 0x4000u) == 0) || ++spins > SPIN_LIMIT;
          if (ready) {
            g = 1;
            if (lane == 0) asm volatile("atom.shared.exch.b32 %0, [%1], 1;" : "=r"(g) : "r"(zorder + 8) : "memory");
            go = __shfl_sync(0xffffffffu, g, 0) == 0;
            break;
          }
          asm volatile("ld.volatile.shared.b32 %0, [%1];" : "=r"(g) : "r"(zorder + 8) : "memory");
          if (g) break;
        }
      }
      if (go) mbar_wait(pub, 0);
      if (go && lane == 0) {
#pragma unroll
        for (int i = 0; i < 4; i++) { mbar_expect_tx(z_full + 8 * i, 16384); bulk_g2s(sbase + ZBUF(i), zq + i * 4096, 16384, z_full + 8 * i); }
      }
      __syncwarp();
    }
    check_batch(sbase + ZBUF(pw), z_full + 8 * pw, zorder, pw, lane);
    if (warp == 12 && lane == 0) g_epoch[blockIdx.x] = epoch + 1;
  } else if (warp >= 8) {
    asm volatile("setmaxnreg.dec.sync.aligned.u32 56;");
    cluster_wait();
    if (warp == 9) {
      for (int k = 1; k < 8; k++) {
        mbar_wait(wb_full + 8 * (k & 1), (k >> 1) & 1);
        mbar_wait(wa_full + 8 * (k & 1), (k >> 1) & 1);
        mbar_wait(eo_full + 8 * (k % 3), (k / 3) & 1);
        asm volatile("bar.sync 1, 160;" ::: "memory");
      }
    } else if (warp == 10) {
      for (int k = 0; k < 8; k++) {
        mbar_wait(eo_full + 8 * (k % 3), (k / 3) & 1);
        if (k >= 2) { mbar_wait(done_loc + 8 * ((k - 2) & 3), ((k - 2) >> 2) & 1); mbar_wait(done_peer + 8 * ((k - 2) & 3), ((k - 2) >> 2) & 1); }
        if (k >= 1 && lane == 0) mbar_expect_tx(sr_full + 8 * (k & 1), ARR_BYTES / 2);
        __syncwarp();
        if (k == 0) asm volatile("bar.sync 8, 288;" ::: "memory");
        else asm volatile("bar.sync 8, 160;" ::: "memory");
      }
    } else if (warp == 11) {
      for (int k = 0; k < 8; k++) {
        if (k >= 1) {
          mbar_wait(sr_full + 8 * (k & 1), (k & 1) ? ((k >> 1) & 1) : (((k >> 1) - 1) & 1));
          asm volatile("fence.proxy.async.shared::cta;" ::: "memory");
        }
        if (k == 0) asm volatile("bar.sync 2, 416;" ::: "memory");
        else asm volatile("bar.sync 2, 288;" ::: "memory");
        if (k == 5) {
          __threadfence();
          if (lane == 0) asm volatile("red.relaxed.gpu.global.add.u32 [%0], 1;" :: "l"(&g_init[tt * 32]) : "memory");
        }
      }
    } else if (lane == 0) {
      auto load_eo = [&](int k) {
        const uint32_t dst = sbase + OFF_EO + (k % 3) * 2 * ARR_SLOT + rank * ARR_SLOT, bar = eo_full + 8 * (k % 3);
        mbar_expect_tx(bar, 2 * ARR_BYTES);
        tma4d_mc(dst, &tmX, k * 64, 2 * rank, u0 - 3, b, bar, (uint16_t)3);
      };
      const int oq = j & 3;
      auto load_wo = [&](int rb, int half, uint32_t dst) {
        tma2d(dst, &tmWo, oq * 128 + half * 64, rb * 128, wo_full + 8 * rb);
      };
      load_eo(1); load_wa(0);
      mbar_wait(eo_full, 0);
      load_wbc(1); load_wa(1); load_eo(2);
      asm volatile("prefetch.tensormap [%0];" :: "l"(&tmWo) : "memory");
      for (int k = 0; k < 6; k++) {
        mbar_wait(wbc_empty + 8 * (k & 1), (k >> 1) & 1);
        load_wbc(k + 2);
        mbar_wait(done_loc + 8 * (k & 3), (k >> 2) & 1);
        load_wa(k + 2);
        if (k + 3 < 8) { mbar_wait(done_peer + 8 * (k & 3), (k >> 2) & 1); load_eo(k + 3); }
      }
      mbar_expect_tx(wo_full, 32768);
      load_wo(0, 0, sbase + OFF_EO + 4 * ARR_SLOT); load_wo(0, 1, sbase + OFF_EO + 4 * ARR_SLOT + 16384);
      mbar_wait(done_loc + 8 * 2, 1);
      mbar_expect_tx(wo_full + 8, 32768);
      load_wo(1, 0, sbase + OFF_EO); load_wo(1, 1, sbase + OFF_EO + 16384);
      mbar_expect_tx(wo_full + 16, 32768);
      load_wo(2, 0, sbase + OFF_W); load_wo(2, 1, sbase + OFF_W + 16384);
      mbar_expect_tx(wo_full + 24, 32768);
      load_wo(3, 0, sbase + OFF_S);
      mbar_wait(wbc_empty + 8, 1);
      load_wo(3, 1, sbase + OFF_W + 5 * W_BYTES + 2 * W_BYTES);
    }
    __syncwarp();
    if (warp == 9) {
      for (int i = 0; i < 4; i++) mbar_wait(wo_full + 8 * i, 0);
      asm volatile("bar.arrive 1, 160;" ::: "memory");
    }
    mbar_wait(done_loc + 8 * 2, 1);
    {
      const int pw = warp - 8;
      uint32_t* zdst = (uint32_t*)g_z + (size_t)(tt * 4) * 32 * 512 + (2 * j + (pw >> 1)) * 512 + (pw & 1) * 32 + lane;
      activation_stream<VG, 2, 16, 384>(sbase, threadIdx.x - 256, zdst, pub, qpub, j >> 2, lane);
    }
  } else if (warp >= 4) {
    asm volatile("setmaxnreg.dec.sync.aligned.u32 72;");
    const int tid = threadIdx.x - 128, hw = warp - 4;
    cluster_wait();
    s0_slice(sbase, hw, lane);
    const uint32_t myoff = rank * (ARR_BYTES / 2) + hw * (ARR_BYTES / 8) + lane * 8;
    const uint32_t s_peer = mapa(sbase + OFF_S, peer), sbar_peer = mapa(sr_full, peer);
    for (int k = 1; k < 8; k++) {
      const uint32_t E = sbase + OFF_EO + (k % 3) * 2 * ARR_SLOT + myoff;
      const uint32_t S = sbase + OFF_S + (k & 1) * ARR_SLOT + myoff;
      const uint32_t Sr = s_peer + (k & 1) * ARR_SLOT + myoff;
      const uint32_t sbar_r = sbar_peer + 8 * (k & 1);
      asm volatile("bar.sync 8, 160;" ::: "memory");
      uint32_t X[2][2], Y[2][2], mx = 0, my = 0;
#pragma unroll
      for (int i = 0; i <= NHALF; i++) {
        if (i < NHALF) {
          asm volatile("bar.sync %0, 256;" :: "r"(EPI_BAR(i)) : "memory");
          asm volatile("ld.shared.v2.b32 {%0,%1}, [%2];" : "=r"(X[i & 1][0]), "=r"(X[i & 1][1]) : "r"(E + i * 256) : "memory");
          asm volatile("ld.shared.v2.b32 {%0,%1}, [%2];" : "=r"(Y[i & 1][0]), "=r"(Y[i & 1][1]) : "r"(E + ARR_SLOT + i * 256) : "memory");
          if (i == MINI_AT && lane < 16) {
            asm volatile("ld.shared.b32 %0, [%1];" : "=r"(mx) : "r"(E - lane * 4 + 2048) : "memory");
            asm volatile("ld.shared.b32 %0, [%1];" : "=r"(my) : "r"(E - lane * 4 + 2048 + ARR_SLOT) : "memory");
          }
        }
        if (i >= 1) {
          const int p = (i - 1) & 1;
          const uint32_t z0 = hadd2_bf16(X[p][0], Y[p][0]), z1 = hadd2_bf16(X[p][1], Y[p][1]);
          asm volatile("st.async.weak.shared::cluster.mbarrier::complete_tx::bytes.v2.b32 [%0], {%1,%2}, [%3];" :: "r"(Sr + (i - 1) * 256), "r"(z0), "r"(z1), "r"(sbar_r) : "memory");
          asm volatile("st.shared.v2.b32 [%0], {%1,%2};" :: "r"(S + (i - 1) * 256), "r"(z0), "r"(z1) : "memory");
          if (i == MINI_AT + 1 && lane < 16) {
            const uint32_t mz = hadd2_bf16(mx, my);
            asm volatile("st.async.weak.shared::cluster.mbarrier::complete_tx::bytes.b32 [%0], %1, [%2];" :: "r"(Sr - lane * 4 + 2048), "r"(mz), "r"(sbar_r) : "memory");
            asm volatile("st.shared.b32 [%0], %1;" :: "r"(S - lane * 4 + 2048), "r"(mz) : "memory");
          }
        }
      }
      asm volatile("fence.proxy.async.shared::cta;" ::: "memory");
      asm volatile("bar.arrive 2, 288;" ::: "memory");
      if (k <= 4) {
        uint4* zi = g_z + ((size_t)(tt * 4) * 32 + 2 * j) * 128 + lane + hw * 32 * 128 + (k - 1) * 64;
#pragma unroll
        for (int i = 0; i < 2; i++)
          asm volatile("st.relaxed.gpu.global.v4.b32 [%0], {%1,%1,%1,%1};" :: "l"(zi + i * 32), "r"(0x40004000u) : "memory");
      }
    }
    {
      uint32_t* zdst = (uint32_t*)g_z + (size_t)(tt * 4) * 32 * 512 + (2 * j + (hw >> 1)) * 512 + (hw & 1) * 32 + lane;
      activation_stream<VG + 1, 2, 16, 384>(sbase, tid, zdst, pub, qpub, j >> 2, lane);
    }
  } else {
    asm volatile("setmaxnreg.inc.sync.aligned.u32 256;");
    float P0[64], P1[64], P2[64];
    const uint32_t lm_off = ((lane >> 3) & 1) * 4096 + (((lane >> 4) * 8 + (lane & 7)) * 64) + ((warp ^ (((lane & 7) >> 1) & 3)) << 4);
    uint32_t Ra[3][4], Rb[3][4], Sm[2][4];
    cluster_wait();
    mbar_wait(w23_full, 0);
    ldsm4t(Ra[0], sbase + OFF_W + 2 * W_BYTES + lm_off); ldsm4t(Rb[0], sbase + OFF_W + 3 * W_BYTES + lm_off);
    const uint32_t done_rem = mapa(done_peer, peer);
    mbar_wait(wb_full, 0);
    mbar_wait(eo_full, 0);
    asm volatile("bar.sync 2, 416;" ::: "memory");
#pragma unroll 1
    for (int k = 0; k < 8; k++) {
      const uint32_t E = sbase + OFF_EO + (k % 3) * 2 * ARR_SLOT;
      const uint32_t W = sbase + OFF_W + (k & 1) * 5 * W_BYTES + lm_off;
      const uint32_t Wn = sbase + OFF_W + ((k + 1) & 1) * 5 * W_BYTES + lm_off;
      const uint64_t dE = make_desc(E, 0, 1024), dO = make_desc(E + ARR_SLOT, 0, 1024);
      const uint64_t dS = make_desc(sbase + OFF_S + (k & 1) * ARR_SLOT, 0, 1024);
#pragma unroll
      for (int gi = 0; gi < 12; gi++) {
        const int type = gi < 8 ? ((gi & 1) ? 2 : 1) : 0;
        const int ks = gi < 8 ? (gi >> 1) : (gi - 8);
        const int ri = gi % 3, si = gi & 1;
        {
          const int gn = (gi + 1) % 12, rn = (gi + 1) % 3;
          const int tn = gn < 8 ? ((gn & 1) ? 2 : 1) : 0, ksn = gn < 8 ? (gn >> 1) : (gn - 8);
          if (gi < 11) {
            const uint32_t base = W + (tn == 0 ? 0 : tn == 1 ? 2 : 4) * W_BYTES + ksn * 1024;
            ldsm4t(Ra[rn], base);
            if (tn != 2) ldsm4t(Rb[rn], base + W_BYTES);
          } else if (k < 7) {
            ldsm4t(Ra[rn], Wn + 2 * W_BYTES); ldsm4t(Rb[rn], Wn + 3 * W_BYTES);
          }
        }
        if (type != 2) {
#pragma unroll
          for (int i = 0; i < 4; i++) Sm[si][i] = hadd2_bf16(Ra[ri][i], Rb[ri][i]);
        }
        const uint64_t sh = (uint64_t)(((type == 0 ? 2 : type == 1 ? 1 : 0) * 256 + ks * 32) >> 4);
        const int sc = (gi == 0) ? (k != 0) : 1;
        wg_fence();
        wgmma_rs_p128(P0, Ra[ri][0], Ra[ri][1], Ra[ri][2], Ra[ri][3], dE + sh, sc);
        if (type != 2) {
          wgmma_rs_p128(P1, Rb[ri][0], Rb[ri][1], Rb[ri][2], Rb[ri][3], dO + sh, sc);
          wgmma_rs_p128(P2, Sm[si][0], Sm[si][1], Sm[si][2], Sm[si][3], dS + sh, sc);
        } else {
          wgmma_rs_p128(P2, Ra[ri][0], Ra[ri][1], Ra[ri][2], Ra[ri][3], dS + sh, 1);
        }
        wg_commit();
        if (gi >= TICK0 && gi < TICK0 + NHALF && k < 7) asm volatile("bar.arrive %0, 256;" :: "r"(EPI_BAR(gi - TICK0)) : "memory");
        if (gi == 5 && k == 0) mbar_wait(wa_full, 0);
        if (gi == 10 && k < 7) asm volatile("bar.sync 1, 160;" ::: "memory");
        if (gi == 11 && k < 7) asm volatile("bar.sync 2, 288;" ::: "memory");
        wg_wait<1>();
        if (gi == 0 && k > 0 && lane == 0) { mbar_arrive(done_loc + 8 * ((k - 1) & 3)); if (k < 7) mbar_arrive_remote(done_rem + 8 * ((k - 1) & 3)); }
        if (gi == 8 && lane == 0) mbar_arrive(wbc_empty + 8 * (k & 1));
      }
    }
    wg_wait<0>();
    fence_regs(P0); fence_regs(P1); fence_regs(P2);
    {
      const uint32_t ybuf = sbase + OFF_Y + threadIdx.x * 16;
      uint32_t zz[2] = {0u, 0u};
#pragma unroll
      for (int jb = 0; jb < 16; jb++) {
        const float one = __uint_as_float(zz[(jb >> 1) & 1] | 0x3F800000u);
        const uint32_t a0 = pack_bf16(P0[4 * jb + 0], P0[4 * jb + 1]), a1 = pack_bf16(P0[4 * jb + 2], P0[4 * jb + 3]);
        const uint32_t a2 = pack_bf16(fmaf(P2[4 * jb + 0], one, -P0[4 * jb + 0]) - P1[4 * jb + 0], fmaf(P2[4 * jb + 1], one, -P0[4 * jb + 1]) - P1[4 * jb + 1]);
        const uint32_t a3 = pack_bf16(fmaf(P2[4 * jb + 2], one, -P0[4 * jb + 2]) - P1[4 * jb + 2], fmaf(P2[4 * jb + 3], one, -P0[4 * jb + 3]) - P1[4 * jb + 3]);
        const uint32_t b0 = pack_bf16(P1[4 * jb + 0], P1[4 * jb + 1]), b1 = pack_bf16(P1[4 * jb + 2], P1[4 * jb + 3]);
        asm volatile("st.shared.v2.b32 [%0], {%1,%2};" :: "r"(sbase + PBUF(jb) + threadIdx.x * 8), "r"(b0), "r"(b1) : "memory");
        asm volatile("st.shared.v4.b32 [%0], {%1,%2,%3,%4};" :: "r"(ybuf + jb * 2048), "r"(a0), "r"(a1), "r"(a2), "r"(a3) : "memory");
        if (jb & 1) {
          if (jb < VG) asm volatile("bar.arrive %0, 256;" :: "r"(EPI_BAR(jb >> 1)) : "memory");
          else asm volatile("bar.arrive %0, 384;" :: "r"(EPI_BAR(jb >> 1)) : "memory");
          if (jb < 12) asm volatile("ld.volatile.shared.b32 %0, [%1];" : "=r"(zz[(jb >> 1) & 1]) : "r"(zero_word) : "memory");
        }
      }
    }
    const int q2 = j >> 2, oq = j & 3;
    __nv_bfloat16* optr[2];
    uint32_t ook;
    {
      const int r = lane >> 2, qq = lane & 3, e = qq & 1;
      const int tl = q2 * 64 + warp * 16 + 4 * (r >> 1) + (r & 1) - 4;
      const int tg = ti * (4 * TILE_U) + tl;
      const bool ok0 = tl >= 0 && tg < T_LEN, ok1 = tl + 2 >= 0 && tg + 2 < T_LEN;
      ook = (ok0 ? 1u : 0u) | (ok1 ? 2u : 0u);
      __nv_bfloat16* base = out + (size_t)b * T_LEN * 512 + oq * 128 + (e ? 8 + 2 * (qq - 1) : 2 * qq);
      optr[0] = base + (size_t)(ok0 ? tg : 0) * 512;
      optr[1] = base + (size_t)(ok1 ? tg + 2 : 0) * 512;
      asm volatile("" : "+l"(optr[0]), "+l"(optr[1]), "+r"(ook));
    }
    asm volatile("bar.sync 1, 160;" ::: "memory");
    float acc2[64];
    {
      const uint32_t* zq = (const uint32_t*)g_z + (size_t)(tt * 4 + q2) * 32 * 512;
      uint32_t spins = 0;
      while (true) {
#pragma unroll
        for (int bt = 0; bt < 4; bt++) {
          asm volatile("bar.sync %0, 160;" :: "r"(LBAR(bt)) : "memory");
          const uint64_t dwo = make_desc(sbase + WOBUF(bt), WOLBO(bt), 1024);
          const uint64_t dz = make_desc<0>(sbase + ZBUF(bt), 128, 256);
          wg_fence();
#pragma unroll
          for (int i = 0; i < 8; i++)
            wgmma_ss_n128_tb(acc2, dz + (uint64_t)(i * (2048 >> 4)), dwo + (uint64_t)(i * (2048 >> 4)), (bt | i) != 0);
          wg_commit();
        }
        wg_wait<0>();
        fence_regs(acc2);
        asm volatile("bar.sync %0, 256;" :: "r"(VBAR) : "memory");
        uint32_t m;
        asm volatile("ld.volatile.shared.b32 %0, [%1];" : "=r"(m) : "r"(zorder) : "memory");
        if (m == 0 || ++spins > SPIN_LIMIT) break;
        asm volatile("bar.sync %0, 256;" :: "r"(VBAR) : "memory");
        if (threadIdx.x == 0) {
          asm volatile("st.volatile.shared.b32 [%0], %1;" :: "r"(zorder), "r"(0u) : "memory");
          for (int i = 0; i < 4; i++)
            if ((m >> i) & 1) {
              mbar_expect_tx(z_full + 8 * i, 16384);
              bulk_g2s(sbase + ZBUF(i), zq + i * 4096, 16384, z_full + 8 * i);
            }
        }
        __syncwarp();
      }
    }
    {
      const bool e = lane & 1;
#pragma unroll
      for (int i = 0; i < 8; i++) {
#pragma unroll
        for (int h = 0; h < 2; h++) {
          const uint32_t u0_ = pack_bf16(acc2[8 * i + 2 * h], acc2[8 * i + 2 * h + 1]);
          const uint32_t u1_ = pack_bf16(acc2[8 * i + 4 + 2 * h], acc2[8 * i + 4 + 2 * h + 1]);
          const uint32_t rcv = __shfl_xor_sync(0xffffffffu, e ? u0_ : u1_, 1);
          if ((ook >> h) & 1) asm volatile("st.global.v2.b32 [%0], {%1,%2};" :: "l"(optr[h] + 16 * i), "r"(e ? rcv : u0_), "r"(e ? u1_ : rcv) : "memory");
        }
      }
    }
  }
}

__global__ void fallback_gate(const __nv_bfloat16* __restrict__ x, const __nv_bfloat16* __restrict__ w) {
  const int ch = blockIdx.x * blockDim.x + threadIdx.x, bt = blockIdx.y, b = bt / T_LEN, t = bt % T_LEN;
  float f = 0.f, g = 0.f;
  for (int i = 0; i < 5; i++) {
    const int ts = t - 2 * i;
    if (ts < 0) break;
    const __nv_bfloat16* xr = x + ((size_t)b * T_LEN + ts) * 512;
    const __nv_bfloat16* wr = w + (size_t)i * 512 * 1024;
    for (int c = 0; c < 512; c++) {
      const float xv = __bfloat162float(xr[c]);
      f = fmaf(xv, __bfloat162float(wr[(size_t)c * 1024 + ch]), f);
      g = fmaf(xv, __bfloat162float(wr[(size_t)c * 1024 + 512 + ch]), g);
    }
  }
  ((__nv_bfloat16*)g_z)[(size_t)bt * 512 + ch] = __float2bfloat16(tanhf(f) / (1.f + expf(-g)));
}
__global__ void fallback_out(const __nv_bfloat16* __restrict__ wo, __nv_bfloat16* __restrict__ out) {
  const int oc = blockIdx.x * blockDim.x + threadIdx.x, bt = blockIdx.y;
  float a = 0.f;
  for (int c = 0; c < 512; c++) a = fmaf(__bfloat162float(((const __nv_bfloat16*)g_z)[(size_t)bt * 512 + c]), __bfloat162float(wo[(size_t)c * 512 + oc]), a);
  out[(size_t)bt * 512 + oc] = __float2bfloat16(a);
}

#define CK(x) (x)
typedef CUresult (*EncFn)(CUtensorMap*, CUtensorMapDataType, cuuint32_t, void*, const cuuint64_t*, const cuuint64_t*,
                          const cuuint32_t*, const cuuint32_t*, CUtensorMapInterleave, CUtensorMapSwizzle,
                          CUtensorMapL2promotion, CUtensorMapFloatOOBfill);

}

extern "C" void kernel_launch(void* const* d_in, const int* in_sizes, int n_in, void* d_out, int out_size) {
  static EncFn enc = nullptr;
  static int mode = -1;
  if (mode < 0) {
    void* fn = nullptr; cudaDriverEntryPointQueryResult qr;
    cudaGetDriverEntryPoint("cuTensorMapEncodeTiled", &fn, cudaEnableDefault, &qr);
    enc = (EncFn)fn;
    cudaFuncSetAttribute(wavenet_kernel, cudaFuncAttributeMaxDynamicSharedMemorySize, SMEM_BYTES);
    cudaLaunchConfig_t cfg = {};
    cfg.gridDim = dim3(128); cfg.blockDim = dim3(NTHREADS); cfg.dynamicSmemBytes = SMEM_BYTES;
    cudaLaunchAttribute at[1];
    at[0].id = cudaLaunchAttributeClusterDimension; at[0].val.clusterDim.x = 2; at[0].val.clusterDim.y = 1; at[0].val.clusterDim.z = 1;
    cfg.attrs = at; cfg.numAttrs = 1;
    int nclusters = 0;
    const cudaError_t e = cudaOccupancyMaxActiveClusters(&nclusters, wavenet_kernel, &cfg);
    if (e != cudaSuccess) (void)cudaGetLastError();
    mode = (enc != nullptr && (e != cudaSuccess || nclusters >= 64)) ? 1 : 0;
  }
  if (mode == 0) {
    fallback_gate<<<dim3(4, 2 * T_LEN), 128, 0, cudaStreamPerThread>>>((const __nv_bfloat16*)d_in[0], (const __nv_bfloat16*)d_in[1]);
    fallback_out<<<dim3(4, 2 * T_LEN), 128, 0, cudaStreamPerThread>>>((const __nv_bfloat16*)d_in[2], (__nv_bfloat16*)d_out);
    return;
  }
  CUtensorMap tmX, tmW, tmWo;
  {
    cuuint64_t dims[4] = {512, 4, 250, 2}; cuuint64_t strides[3] = {1024, 4096, 1024000}; cuuint32_t box[4] = {64, 2, 66, 1}; cuuint32_t es[4] = {1, 1, 1, 1};
    CK(enc(&tmX, CU_TENSOR_MAP_DATA_TYPE_BFLOAT16, 4, d_in[0], dims, strides, box, es, CU_TENSOR_MAP_INTERLEAVE_NONE,
        CU_TENSOR_MAP_SWIZZLE_128B, CU_TENSOR_MAP_L2_PROMOTION_L2_128B, CU_TENSOR_MAP_FLOAT_OOB_FILL_NONE));
  }
  {
    cuuint64_t dims[3] = {512, 2560, 2}; cuuint64_t strides[2] = {2048, 1024}; cuuint32_t box[3] = {32, 64, 2}; cuuint32_t es[3] = {1, 1, 1};
    CK(enc(&tmW, CU_TENSOR_MAP_DATA_TYPE_BFLOAT16, 3, d_in[1], dims, strides, box, es, CU_TENSOR_MAP_INTERLEAVE_NONE,
        CU_TENSOR_MAP_SWIZZLE_64B, CU_TENSOR_MAP_L2_PROMOTION_L2_128B, CU_TENSOR_MAP_FLOAT_OOB_FILL_NONE));
  }
  {
    cuuint64_t dims[2] = {512, 512}; cuuint64_t strides[1] = {1024}; cuuint32_t box[2] = {64, 128}; cuuint32_t es[2] = {1, 1};
    CK(enc(&tmWo, CU_TENSOR_MAP_DATA_TYPE_BFLOAT16, 2, d_in[2], dims, strides, box, es, CU_TENSOR_MAP_INTERLEAVE_NONE,
        CU_TENSOR_MAP_SWIZZLE_128B, CU_TENSOR_MAP_L2_PROMOTION_L2_128B, CU_TENSOR_MAP_FLOAT_OOB_FILL_NONE));
  }
  wavenet_kernel<<<128, NTHREADS, SMEM_BYTES, cudaStreamPerThread>>>(tmX, tmW, tmWo, (__nv_bfloat16*)d_out);
}
```
